```python
import torch

def _softmax(x, axis=-1):
    return torch.softmax(x, dim=axis)

def _gelu(x):
    return torch.nn.functional.gelu(x, approximate='tanh')

def _silu(x):
    return torch.nn.functional.silu(x)

def _sigmoid(x):
    return torch.sigmoid(x)

def _layernorm(x, axis=-1, eps=1e-05):
    m = x.mean(dim=axis, keepdim=True)
    v = x.var(dim=axis, keepdim=True, unbiased=False)
    return (x - m) / torch.sqrt(v + eps)

def _scatter_add(tgt, idx, src, axis=0):
    return tgt.clone().index_add_(axis, idx, src)

def _segment_sum(src, seg, n):
    out = torch.zeros((n,) + src.shape[1:], dtype=src.dtype)
    return out.index_add_(0, seg, src)

def _pad(x, pw):
    flat = tuple((v for pair in reversed(pw) for v in pair))
    return torch.nn.functional.pad(x, flat)
kernel_name = 'adaLN_cond__gqa_block_cached__geglu_ffn__decode'

def setup_inputs():

    _w = lambda a: (lambda t: t.to(torch.bfloat16) if t.is_floating_point() else t)(torch.as_tensor(a))

    def _A_setup():
        B, Sq, D = (4, 1, 512)
        Hq, Hkv, Sk, Dh = (32, 8, 8192, 128)
        assert Hq % Hkv == 0, (Hq, Hkv)
        return {'x': _w((lambda *s: torch.randn(*s, dtype=torch.bfloat16) * 0.1)(B, Sq, D)), 'k_cache': _w((lambda *s: torch.randn(*s, dtype=torch.bfloat16) * 0.8)(B, Hkv, Sk, Dh)), 'v_cache': _w((lambda *s: torch.randn(*s, dtype=torch.bfloat16) * 1.6)(B, Hkv, Sk, Dh)), 'wq': _w((lambda *s: torch.randn(*s, dtype=torch.bfloat16) * 0.8)(D, Hq * Dh) * D ** (-0.5)), 'wo': _w((lambda *s: torch.randn(*s, dtype=torch.bfloat16) * 1.6)(Hq * Dh, D) * (Hq * Dh) ** (-0.5))}
    _A_in = _A_setup()

    def _B_setup():
        B, S, D, F = (4, 1, 512, 1792)
        return {'x': _w((lambda *s: torch.randn(*s, dtype=torch.bfloat16) * 0.1)(B, S, D)), 'w_gate': _w((lambda *s: torch.randn(*s, dtype=torch.bfloat16) * 0.1)(D, F)), 'w_up': _w((lambda *s: torch.randn(*s, dtype=torch.bfloat16) * 0.1)(D, F)), 'w_down': _w((lambda *s: torch.randn(*s, dtype=torch.bfloat16) * 0.1)(F, D))}
    _B_in = _B_setup()
    return {'A_x': _A_in['x'], 'A_k_cache': _A_in['k_cache'], 'A_v_cache': _A_in['v_cache'], 'A_wq': _A_in['wq'], 'A_wo': _A_in['wo'], 'B_x': _B_in['x'], 'B_w_gate': _B_in['w_gate'], 'B_w_up': _B_in['w_up'], 'B_w_down': _B_in['w_down'], 'c': _w((lambda *s: torch.randn(*s, dtype=torch.bfloat16) * 0.8)(4, 512) * 8.0), 'w_mod': _w((lambda *s: torch.randn(*s, dtype=torch.bfloat16) * 0.8)(512, 6 * 512) * 512 ** (-0.5) * 8.0)}

def reference(A_x, A_k_cache, A_v_cache, A_wq, A_wo, B_x, B_w_gate, B_w_up, B_w_down, c, w_mod):

    def _A_ref(x, k_cache, v_cache, wq, wo):
        B, Sq, D = x.shape
        Hq, Dh = (32, 128)
        Hkv = k_cache.shape[1]
        rep = Hq // Hkv
        q = (lambda x, *d: x.permute(*d))((x @ wq).reshape(B, Sq, Hq, Dh), 0, 2, 1, 3)
        k = (lambda x, n, axis: torch.repeat_interleave(x, n, dim=axis))(k_cache, rep, axis=1)
        v = (lambda x, n, axis: torch.repeat_interleave(x, n, dim=axis))(v_cache, rep, axis=1)
        scores = torch.einsum('bhqd,bhkd->bhqk', q, k) * Dh ** (-0.5)
        p = _softmax(scores, axis=-1)
        o = torch.einsum('bhqk,bhkd->bhqd', p, v)
        return (lambda x, *d: x.permute(*d))(o, 0, 2, 1, 3).reshape(B, Sq, Hq * Dh) @ wo

    def _B_ref(x, w_gate, w_up, w_down):
        return _gelu(x @ w_gate) * (x @ w_up) @ w_down
    x = A_x
    mod = (_silu(c) @ w_mod).reshape(c.shape[0], 6, 1, -1)
    sa, ca, ga, sb, cb, gb = (mod[:, 0].clone(), mod[:, 1].clone(), mod[:, 2].clone(), mod[:, 3].clone(), mod[:, 4].clone(), mod[:, 5].clone())
    h = _layernorm(x, axis=-1) * (1 + ca) + sa
    x = x + ga * _A_ref(h, A_k_cache, A_v_cache, A_wq, A_wo)
    h = _layernorm(x, axis=-1) * (1 + cb) + sb
    x = x + gb * _B_ref(h, B_w_gate, B_w_up, B_w_down)
    return x
```

```cpp
#include <cuda_runtime.h>
#include <cuda_bf16.h>
#include <cuda.h>
#include <stdint.h>

typedef __nv_bfloat16 bf16;

namespace {

constexpr int NB = 4, DM = 512, HQ = 32, HKV = 8, SK = 8192, DH = 128, FF = 1792;
constexpr int NCTA = 128;
constexpr int NSLOT = 12;
constexpr int SLOT = 16384;
constexpr int TK = 64;
constexpr int NTILE = 32;
constexpr int NKV = 2 * NTILE;
constexpr int INFLIGHT = 4;
constexpr int NFFN = FF / 16;
constexpr int NTHREADS = 320;
constexpr unsigned SPIN_LIMIT = 1u << 22;
constexpr float LOG2E = 1.4426950408889634f;

struct __align__(128) Scratch {
    uint32_t q[NB * HQ * 64];
    uint32_t sbcb[2 * NB * 256];
    uint32_t po[HQ * NB * 4 * DH];
    uint32_t pml[HQ * NB * 4 * 2];
    uint32_t wop[HQ * NB * DM];
    uint32_t x1[NB * 256];
    uint32_t dnp[NFFN * DM * NB];
    uint32_t pad[1024];
};
static_assert(sizeof(Scratch) % (NCTA * 16) == 0, "scratch must split evenly");
__device__ Scratch g_scr;
__device__ __align__(128) uint32_t g_h[NCTA * 8];
#define STAMP(i) do {} while (0)

constexpr int OFF_RING = 0;
constexpr int OFF_MRG = NSLOT * SLOT;
constexpr int OFF_ML = OFF_MRG + 8 * 4 * 132 * 4;
constexpr int OFF_RED = OFF_ML + 8 * 4 * 2 * 4;
constexpr int OFF_RED2 = OFF_RED + 8 * 128 * 4;
constexpr int OFF_SO = OFF_RED2 + 8 * 96 * 4;
constexpr int OFF_H2 = OFF_SO + 4 * 136 * 2;
constexpr int OFF_ACT = OFF_H2 + 4 * 520 * 2;
constexpr int OFF_LOC = OFF_ACT + 4 * 24 * 2;
constexpr int OFF_BAR = OFF_LOC + 64 * 4;
constexpr int SMEM_USED = OFF_BAR + 2 * NSLOT * 8;
constexpr int SMEM_BYTES = SMEM_USED + 1024;
static_assert(SMEM_BYTES <= 232448, "too much smem");
static_assert(OFF_BAR % 8 == 0 && OFF_SO % 16 == 0 && OFF_H2 % 16 == 0 && OFF_ACT % 16 == 0, "align");

__device__ __forceinline__ uint32_t smem_u32(const void* p) { return (uint32_t)__cvta_generic_to_shared(p); }
__device__ __forceinline__ void mbar_init(uint32_t bar, int cnt) { asm volatile("mbarrier.init.shared::cta.b64 [%0], %1;" ::"r"(bar), "r"(cnt) : "memory"); }
__device__ __forceinline__ void mbar_expect_tx(uint32_t bar, uint32_t bytes) { asm volatile("mbarrier.arrive.expect_tx.shared::cta.b64 _, [%0], %1;" ::"r"(bar), "r"(bytes) : "memory"); }
__device__ __forceinline__ void mbar_arrive(uint32_t bar) { asm volatile("mbarrier.arrive.shared::cta.b64 _, [%0];" ::"r"(bar) : "memory"); }
__device__ __forceinline__ bool mbar_try(uint32_t bar, uint32_t parity) {
    uint32_t ok;
    asm volatile("{\n.reg .pred p;\nmbarrier.try_wait.parity.shared::cta.b64 p, [%1], %2;\nselp.u32 %0, 1, 0, p;\n}" : "=r"(ok) : "r"(bar), "r"(parity) : "memory");
    return ok != 0;
}
__device__ __forceinline__ void mbar_wait(uint32_t bar, uint32_t parity) {
    unsigned it = 0;
    while (!mbar_try(bar, parity)) { if (++it > SPIN_LIMIT) break; }
}
__device__ __forceinline__ void tma2d(uint32_t dst, const CUtensorMap* m, int c0, int c1, uint32_t bar) {
    asm volatile("cp.async.bulk.tensor.2d.shared::cluster.global.mbarrier::complete_tx::bytes [%0], [%1, {%3, %4}], [%2];" ::"r"(dst), "l"(m), "r"(bar), "r"(c0), "r"(c1) : "memory");
}
__device__ __forceinline__ void tma3d(uint32_t dst, const CUtensorMap* m, int c0, int c1, int c2, uint32_t bar) {
    asm volatile("cp.async.bulk.tensor.3d.shared::cluster.global.mbarrier::complete_tx::bytes [%0], [%1, {%3, %4, %5}], [%2];" ::"r"(dst), "l"(m), "r"(bar), "r"(c0), "r"(c1), "r"(c2) : "memory");
}
__device__ __forceinline__ void tma3d_hint(uint32_t dst, const CUtensorMap* m, int c0, int c1, int c2, uint32_t bar, uint64_t pol) {
    asm volatile("cp.async.bulk.tensor.3d.shared::cluster.global.mbarrier::complete_tx::bytes.L2::cache_hint [%0], [%1, {%3, %4, %5}], [%2], %6;" ::"r"(dst), "l"(m), "r"(bar), "r"(c0), "r"(c1), "r"(c2), "l"(pol) : "memory");
}
__device__ __forceinline__ void bar_sync(int id, int n) { asm volatile("bar.sync %0, %1;" ::"r"(id), "r"(n) : "memory"); }
__device__ __forceinline__ void bar_arrive(int id, int n) { asm volatile("bar.arrive %0, %1;" ::"r"(id), "r"(n) : "memory"); }
__device__ __forceinline__ void ldsm4(uint32_t* r, uint32_t addr) {
    asm volatile("ldmatrix.sync.aligned.m8n8.x4.shared.b16 {%0,%1,%2,%3}, [%4];" : "=r"(r[0]), "=r"(r[1]), "=r"(r[2]), "=r"(r[3]) : "r"(addr) : "memory");
}
__device__ __forceinline__ void ldsm4t(uint32_t* r, uint32_t addr) {
    asm volatile("ldmatrix.sync.aligned.m8n8.x4.trans.shared.b16 {%0,%1,%2,%3}, [%4];" : "=r"(r[0]), "=r"(r[1]), "=r"(r[2]), "=r"(r[3]) : "r"(addr) : "memory");
}
__device__ __forceinline__ void ldsm2(uint32_t* r, uint32_t addr) {
    asm volatile("ldmatrix.sync.aligned.m8n8.x2.shared.b16 {%0,%1}, [%2];" : "=r"(r[0]), "=r"(r[1]) : "r"(addr) : "memory");
}
__device__ __forceinline__ void mma16816(float* d, const uint32_t* a, uint32_t b0, uint32_t b1) {
    asm volatile("mma.sync.aligned.m16n8k16.row.col.f32.bf16.bf16.f32 {%0,%1,%2,%3}, {%4,%5,%6,%7}, {%8,%9}, {%0,%1,%2,%3};"
                 : "+f"(d[0]), "+f"(d[1]), "+f"(d[2]), "+f"(d[3]) : "r"(a[0]), "r"(a[1]), "r"(a[2]), "r"(a[3]), "r"(b0), "r"(b1));
}
__device__ __forceinline__ uint32_t movmat(uint32_t a) {
    uint32_t d;
    asm volatile("movmatrix.sync.aligned.m8n8.trans.b16 %0, %1;" : "=r"(d) : "r"(a));
    return d;
}
__device__ __forceinline__ uint32_t pack_bf16(float lo, float hi) {
    uint32_t r;
    asm("cvt.rn.bf16x2.f32 %0, %1, %2;" : "=r"(r) : "f"(hi), "f"(lo));
    return r;
}
__device__ __forceinline__ float rbf(float x) { return __bfloat162float(__float2bfloat16_rn(x)); }
__device__ __forceinline__ float bf_lo(uint32_t w) { return __uint_as_float(w << 16); }
__device__ __forceinline__ float bf_hi(uint32_t w) { return __uint_as_float(w & 0xffff0000u); }
__device__ __forceinline__ float ex2(float x) { float y; asm("ex2.approx.ftz.f32 %0, %1;" : "=f"(y) : "f"(x)); return y; }
__device__ __forceinline__ uint32_t nz(uint32_t w) { return w ? w : 0x80000000u; }
__device__ __forceinline__ uint32_t nzf(float f) { return nz(__float_as_uint(f)); }
__device__ __forceinline__ uint2 ldg64(const void* p) {
    uint2 v;
    asm volatile("ld.global.nc.L1::no_allocate.v2.u32 {%0,%1}, [%2];" : "=r"(v.x), "=r"(v.y) : "l"(p));
    return v;
}
__device__ __forceinline__ uint4 ldg128(const void* p) {
    uint4 v;
    asm volatile("ld.global.nc.L1::no_allocate.v4.u32 {%0,%1,%2,%3}, [%4];" : "=r"(v.x), "=r"(v.y), "=r"(v.z), "=r"(v.w) : "l"(p));
    return v;
}
__device__ __forceinline__ uint4 ldx128(const void* p) {
    uint4 v;
    asm volatile("ld.relaxed.gpu.global.v4.u32 {%0,%1,%2,%3}, [%4];" : "=r"(v.x), "=r"(v.y), "=r"(v.z), "=r"(v.w) : "l"(p) : "memory");
    return v;
}
__device__ __forceinline__ uint2 ldx64(const void* p) {
    uint2 v;
    asm volatile("ld.relaxed.gpu.global.v2.u32 {%0,%1}, [%2];" : "=r"(v.x), "=r"(v.y) : "l"(p) : "memory");
    return v;
}
__device__ __forceinline__ void stx32(void* p, uint32_t v) { asm volatile("st.relaxed.gpu.global.u32 [%0], %1;" ::"l"(p), "r"(v) : "memory"); }
__device__ __forceinline__ void stx64(void* p, uint32_t a, uint32_t b) { asm volatile("st.relaxed.gpu.global.v2.u32 [%0], {%1,%2};" ::"l"(p), "r"(a), "r"(b) : "memory"); }
__device__ __forceinline__ bool ok4(const uint4& v) { return v.x && v.y && v.z && v.w; }
__device__ __forceinline__ bool ok2(const uint2& v) { return v.x && v.y; }

template <int N>
__device__ __forceinline__ void bfly(float* a, int lane, int off) {
    const bool up = (lane & off) != 0;
#pragma unroll
    for (int i = 0; i < N / 2; i++) {
        float send = up ? a[i] : a[i + N / 2];
        float keep = up ? a[i + N / 2] : a[i];
        a[i] = keep + __shfl_xor_sync(0xffffffffu, send, off);
    }
}
__device__ __forceinline__ float warp_sum(float v) {
#pragma unroll
    for (int o = 16; o; o >>= 1) v += __shfl_xor_sync(0xffffffffu, v, o);
    return v;
}
__device__ __forceinline__ void ln_stats(const float* v, float& mean_b, float& sd_b) {
    float s = 0.f;
#pragma unroll
    for (int i = 0; i < 16; i++) s += v[i];
    float mean = warp_sum(s) * (1.0f / DM);
    float q = 0.f;
#pragma unroll
    for (int i = 0; i < 16; i++) { float d = v[i] - mean; q += d * d; }
    float var = warp_sum(q) * (1.0f / DM);
    mean_b = rbf(mean);
    sd_b = rbf(sqrtf(rbf(rbf(var) + 1e-5f)));
}
__device__ __forceinline__ float ln_mod(float x, float mean_b, float sd_b, float one_plus_c, float sh) {
    float n = rbf(__fdiv_rn(rbf(x - mean_b), sd_b));
    return rbf(rbf(n * one_plus_c) + sh);
}
__device__ __forceinline__ void unpack8(const uint4& v, float* f) {
    f[0] = bf_lo(v.x); f[1] = bf_hi(v.x); f[2] = bf_lo(v.y); f[3] = bf_hi(v.y);
    f[4] = bf_lo(v.z); f[5] = bf_hi(v.z); f[6] = bf_lo(v.w); f[7] = bf_hi(v.w);
}

__global__ void __launch_bounds__(NTHREADS, 1)
fused_kernel(const __grid_constant__ CUtensorMap tmK, const __grid_constant__ CUtensorMap tmV,
             const __grid_constant__ CUtensorMap tmWo, const __grid_constant__ CUtensorMap tmG,
             const __grid_constant__ CUtensorMap tmU, const __grid_constant__ CUtensorMap tmD,
             const bf16* __restrict__ x, const bf16* __restrict__ wq, const bf16* __restrict__ cvec,
             const bf16* __restrict__ wmod, bf16* __restrict__ out) {
    extern __shared__ uint8_t smem_raw[];
    const uint32_t sbase = (smem_u32(smem_raw) + 1023u) & ~1023u;
    uint8_t* sptr = smem_raw + (sbase - smem_u32(smem_raw));
    const int tid = threadIdx.x, lane = tid & 31, warp = tid >> 5;
    const int cta = blockIdx.x;
    const uint32_t bar_full = sbase + OFF_BAR, bar_empty = bar_full + NSLOT * 8;

    if (warp == 8) {
        if (lane == 0) {
            uint64_t pol;
            asm volatile("createpolicy.fractional.L2::evict_first.b64 %0, 1.0;" : "=l"(pol));
            const int row0 = cta * (NTILE * TK);
#pragma unroll
            for (int i = 0; i < INFLIGHT; i++) mbar_init(bar_full + i * 8, 1);
            asm volatile("fence.mbarrier_init.release.cluster;" ::: "memory");
#pragma unroll
            for (int i = 0; i < INFLIGHT; i++) {
                mbar_expect_tx(bar_full + i * 8, SLOT);
                tma3d_hint(sbase + i * SLOT, (i & 1) ? &tmV : &tmK, 0, row0 + (i >> 1) * TK, 0, bar_full + i * 8, pol);
            }
            for (int i = INFLIGHT; i < NSLOT; i++) mbar_init(bar_full + i * 8, 1);
            for (int i = 0; i < NSLOT; i++) mbar_init(bar_empty + i * 8, 4);
            asm volatile("fence.mbarrier_init.release.cluster;" ::: "memory");
            asm volatile("prefetch.tensormap [%0];" ::"l"(&tmWo) : "memory");
            asm volatile("prefetch.tensormap [%0];" ::"l"(&tmG) : "memory");
            asm volatile("prefetch.tensormap [%0];" ::"l"(&tmU) : "memory");
            asm volatile("prefetch.tensormap [%0];" ::"l"(&tmD) : "memory");
        }
        __syncwarp();
        bar_arrive(3, 288);
        if (lane == 0) {
            uint64_t pol;
            asm volatile("createpolicy.fractional.L2::evict_first.b64 %0, 1.0;" : "=l"(pol));
            const int row0 = cta * (NTILE * TK);
            const int nitems = NKV + ((cta < NFFN) ? 5 : 2);
            int slot = INFLIGHT, ph = 0;
            int wslot = 0, wph = 0;
            for (int i = INFLIGHT; i < nitems; i++) {
                mbar_wait(bar_full + wslot * 8, wph);
                mbar_wait(bar_empty + slot * 8, ph ^ 1);
                const uint32_t dst = sbase + slot * SLOT, fb = bar_full + slot * 8;
                mbar_expect_tx(fb, SLOT);
                if (i < NKV) {
                    tma3d_hint(dst, (i & 1) ? &tmV : &tmK, 0, row0 + (i >> 1) * TK, 0, fb, pol);
                } else if (i < NKV + 2) {
                    tma2d(dst, &tmWo, (cta & 3) * 128 + (i - NKV) * 64, (cta >> 2) * 128, fb);
                } else if (i < NKV + 4) {
                    const CUtensorMap* m = (i == NKV + 2) ? &tmG : &tmU;
                    tma2d(dst, m, cta * 16, 0, fb);
                    tma2d(dst + 8192, m, cta * 16, 256, fb);
                } else {
                    tma3d(dst, &tmD, 0, cta * 16, 0, fb);
                }
                if (++slot == NSLOT) { slot = 0; ph ^= 1; }
                if (++wslot == NSLOT) { wslot = 0; wph ^= 1; }
            }
        }
        return;
    }

    float* s_red = reinterpret_cast<float*>(sptr + OFF_RED);
    float* s_red2 = reinterpret_cast<float*>(sptr + OFF_RED2);
    float* s_loc = reinterpret_cast<float*>(sptr + OFF_LOC);

    if (warp == 9) {
        uint4 xv[NB][2];
#pragma unroll
        for (int b = 0; b < NB; b++) {
            xv[b][0] = ldg128(x + b * DM + lane * 8);
            xv[b][1] = ldg128(x + b * DM + 256 + lane * 8);
        }
        const int ob = (lane >> 2) & 3, oc = lane & 3;
        const float xown = __bfloat162float(x[ob * DM + cta * 4 + oc]);
        {
            constexpr int N16 = sizeof(Scratch) / 16 / NCTA;
            uint4* p = reinterpret_cast<uint4*>(&g_scr) + (size_t)cta * N16;
            const uint4 z = make_uint4(0, 0, 0, 0);
            for (int i = lane; i < N16; i += 32) p[i] = z;
        }
        float mean_o = 0.f, sd_o = 1.f;
#pragma unroll
        for (int b = 0; b < NB; b++) {
            float v[16], mb, sb_;
            unpack8(xv[b][0], v);
            unpack8(xv[b][1], v + 8);
            ln_stats(v, mb, sb_);
            if (b == ob) { mean_o = mb; sd_o = sb_; }
        }
        __threadfence();
        bar_sync(1, 288);
        {
            float sa = 0.f, ca = 0.f;
#pragma unroll
            for (int w = 0; w < 8; w++) {
                sa += s_red2[w * 96 + oc * 4 + ob];
                ca += s_red2[w * 96 + 16 + oc * 4 + ob];
            }
            float h = ln_mod(xown, mean_o, sd_o, rbf(1.0f + rbf(ca)), rbf(sa));
            float hn = __shfl_down_sync(0xffffffffu, h, 1);
            if (lane < 16 && !(lane & 1)) stx32(&g_h[cta * 8 + (lane >> 1)], nz(pack_bf16(h, hn)));
        }
        bar_sync(2, 288);
        {
            const int hi = lane >> 4;
            float u0 = 0.f, u1 = 0.f;
#pragma unroll
            for (int w = 0; w < 8; w++) {
                u0 += s_red2[w * 96 + 32 + hi * 32 + oc * 4 + ob];
                u1 += s_red2[w * 96 + 48 + hi * 32 + oc * 4 + ob];
            }
            u0 = rbf(u0); u1 = rbf(u1);
            float pub = hi ? rbf(1.0f + u0) : u1;
            float pn = __shfl_down_sync(0xffffffffu, pub, 1);
            s_loc[hi * 16 + (lane & 15)] = hi ? u1 : u0;
            if (!hi) s_loc[32 + lane] = xown;
            bar_sync(6, 288);
            if (!(lane & 1)) stx32(&g_scr.sbcb[hi * (NB * 256) + ob * 256 + cta * 2 + (oc >> 1)], nz(pack_bf16(pub, pn)));
        }
        return;
    }

    const int g = lane >> 2, t = lane & 3;
    STAMP(0);
    uint2 wm[6][2];
    float sc[NB][2];
    {
        unsigned short cr[NB][2];
#pragma unroll
        for (int h = 0; h < 2; h++)
#pragma unroll
            for (int v = 0; v < 2; v++) wm[v][h] = ldg64(wmod + (size_t)(tid + 256 * h) * (6 * DM) + v * DM + cta * 4);
#pragma unroll
        for (int b = 0; b < NB; b++)
#pragma unroll
            for (int h = 0; h < 2; h++) cr[b][h] = __ldg(reinterpret_cast<const unsigned short*>(cvec) + b * DM + tid + 256 * h);
#pragma unroll
        for (int b = 0; b < NB; b++)
#pragma unroll
            for (int h = 0; h < 2; h++) sc[b][h] = __uint_as_float((uint32_t)cr[b][h] << 16);
    }
    uint2 wqv[4][4];
#pragma unroll
    for (int ks = 0; ks < 4; ks++)
#pragma unroll
        for (int i = 0; i < 4; i++)
            wqv[ks][i] = ldg64(wq + (size_t)(4 * (16 * warp + 4 * ks + t) + i) * (HQ * DH) + cta * 32 + g * 4);
#pragma unroll
    for (int h = 0; h < 2; h++)
#pragma unroll
        for (int v = 2; v < 6; v++) wm[v][h] = ldg64(wmod + (size_t)(tid + 256 * h) * (6 * DM) + v * DM + cta * 4);
#pragma unroll
    for (int b = 0; b < NB; b++)
#pragma unroll
        for (int h = 0; h < 2; h++) { float c = sc[b][h]; sc[b][h] = rbf(__fdiv_rn(c, 1.0f + expf(-c))); }

#pragma unroll
    for (int grp = 0; grp < 3; grp++) {
        float a[32];
#pragma unroll
        for (int vv = 0; vv < 2; vv++) {
            const int v = grp * 2 + vv;
            float w0[4] = {bf_lo(wm[v][0].x), bf_hi(wm[v][0].x), bf_lo(wm[v][0].y), bf_hi(wm[v][0].y)};
            float w1[4] = {bf_lo(wm[v][1].x), bf_hi(wm[v][1].x), bf_lo(wm[v][1].y), bf_hi(wm[v][1].y)};
#pragma unroll
            for (int c = 0; c < 4; c++)
#pragma unroll
                for (int b = 0; b < NB; b++) a[vv * 16 + c * 4 + b] = fmaf(sc[b][1], w1[c], sc[b][0] * w0[c]);
        }
        bfly<32>(a, lane, 16);
        bfly<16>(a, lane, 8);
        bfly<8>(a, lane, 4);
        bfly<4>(a, lane, 2);
        bfly<2>(a, lane, 1);
        s_red2[warp * 96 + grp * 32 + lane] = a[0];
        if (grp == 0) bar_arrive(1, 288);
    }
    bar_arrive(2, 288);
    STAMP(1);

    {
        uint32_t af[4][2][4];
#pragma unroll
        for (int ks = 0; ks < 4; ks++) {
            af[ks][0][0] = __byte_perm(wqv[ks][0].x, wqv[ks][1].x, 0x5410);
            af[ks][0][1] = __byte_perm(wqv[ks][0].x, wqv[ks][1].x, 0x7632);
            af[ks][0][2] = __byte_perm(wqv[ks][2].x, wqv[ks][3].x, 0x5410);
            af[ks][0][3] = __byte_perm(wqv[ks][2].x, wqv[ks][3].x, 0x7632);
            af[ks][1][0] = __byte_perm(wqv[ks][0].y, wqv[ks][1].y, 0x5410);
            af[ks][1][1] = __byte_perm(wqv[ks][0].y, wqv[ks][1].y, 0x7632);
            af[ks][1][2] = __byte_perm(wqv[ks][2].y, wqv[ks][3].y, 0x5410);
            af[ks][1][3] = __byte_perm(wqv[ks][2].y, wqv[ks][3].y, 0x7632);
        }
        uint2 hv[4];
        {
            const uint32_t* hp = g_h + (16 * warp + t) * 8 + (g & 3) * 2;
            unsigned it = 0;
            bool ok;
            do {
#pragma unroll
                for (int ks = 0; ks < 4; ks++) hv[ks] = ldx64(hp + ks * 32);
                ok = ok2(hv[0]) && ok2(hv[1]) && ok2(hv[2]) && ok2(hv[3]);
            } while (!ok && ++it < SPIN_LIMIT);
        }
        __syncwarp();
        float d[2][4] = {{0.f, 0.f, 0.f, 0.f}, {0.f, 0.f, 0.f, 0.f}};
#pragma unroll
        for (int ks = 0; ks < 4; ks++) {
            mma16816(d[0], af[ks][0], hv[ks].x, hv[ks].y);
            mma16816(d[1], af[ks][1], hv[ks].x, hv[ks].y);
        }
        if (t < 2) {
            float4* p0 = reinterpret_cast<float4*>(s_red + warp * 128 + (2 * t) * 32 + 4 * g);
            float4* p1 = reinterpret_cast<float4*>(s_red + warp * 128 + (2 * t + 1) * 32 + 4 * g);
            *p0 = make_float4(d[0][0], d[0][2], d[1][0], d[1][2]);
            *p1 = make_float4(d[0][1], d[0][3], d[1][1], d[1][3]);
        }
        __threadfence();
        bar_sync(6, 288);
        if (tid < 64) {
            const int b = tid >> 4, cp = tid & 15;
            float s0 = 0.f, s1 = 0.f;
#pragma unroll
            for (int w = 0; w < 8; w++) {
                float2 v = *reinterpret_cast<const float2*>(s_red + w * 128 + b * 32 + 2 * cp);
                s0 += v.x; s1 += v.y;
            }
            const int tt = cp & 3, hi = (cp >> 2) & 1, ksl = cp >> 3;
            stx32(&g_scr.q[(b * HQ + (cta >> 2)) * 64 + (cta & 3) * 16 + tt * 4 + ksl * 2 + hi], nz(pack_bf16(s0, s1)));
        }
    }
    STAMP(2);

    const int pair = cta >> 2, split = cta & 3;
    const int ab = pair >> 3, kvh = pair & 7;
    uint32_t qf[8][2];
    uint4 sbv, cbv;
    {
        const uint32_t* qp = g_scr.q + (ab * HQ + kvh * 4 + (g & 3)) * 64 + t * 4;
        const uint32_t* sp = g_scr.sbcb + (warp & 3) * 256 + (warp >> 2) * 128 + lane * 4;
        uint4 qv[4];
        unsigned it = 0;
        bool ok;
        do {
#pragma unroll
            for (int i = 0; i < 4; i++) qv[i] = ldx128(qp + i * 16);
            sbv = ldx128(sp);
            cbv = ldx128(sp + NB * 256);
            ok = ok4(qv[0]) && ok4(qv[1]) && ok4(qv[2]) && ok4(qv[3]) && ok4(sbv) && ok4(cbv);
        } while (!ok && ++it < SPIN_LIMIT);
#pragma unroll
        for (int i = 0; i < 4; i++) {
            const bool z = g >= 4;
            qf[2 * i][0] = z ? 0u : qv[i].x;
            qf[2 * i][1] = z ? 0u : qv[i].y;
            qf[2 * i + 1][0] = z ? 0u : qv[i].z;
            qf[2 * i + 1][1] = z ? 0u : qv[i].w;
        }
    }
    bar_sync(3, 288);
    STAMP(3);

    float o[8][4];
#pragma unroll
    for (int i = 0; i < 8; i++) { o[i][0] = o[i][1] = o[i][2] = o[i][3] = 0.f; }
    float m0 = -INFINITY, m1 = -INFINITY, l0 = 0.f, l1 = 0.f;
    {
        const int grp = warp >> 2, r0 = (warp & 3) * 16;
        const int krow = r0 + (lane & 7) + ((lane >> 3) & 1) * 8;
        const int vrow = r0 + (lane & 7) + (lane >> 4) * 8;
        const uint32_t koff = krow * 128, kx = krow & 7, kc = lane >> 4;
        const uint32_t voff = vrow * 128, vx = vrow & 7, vc = (lane >> 3) & 1;
        int slot = 2 * grp, ph = 0;
        const float scale = 0.08838834764831845f;
        for (int j = grp; j < NTILE; j += 2) {
            const uint32_t kb = sbase + slot * SLOT, vb = kb + SLOT;
            mbar_wait(bar_full + slot * 8, ph);
            float s[2][4] = {{0.f, 0.f, 0.f, 0.f}, {0.f, 0.f, 0.f, 0.f}};
#pragma unroll
            for (int ks = 0; ks < 8; ks++) {
                uint32_t a[4];
                ldsm4(a, kb + (ks >> 2) * 8192 + koff + ((((ks & 3) * 2 + kc) ^ kx) << 4));
                mma16816(s[ks & 1], a, qf[ks][0], qf[ks][1]);
            }
            __syncwarp();
            if (lane == 0) mbar_arrive(bar_empty + slot * 8);
            float sv[4];
#pragma unroll
            for (int i = 0; i < 4; i++) sv[i] = rbf(rbf(s[0][i] + s[1][i]) * scale);
            float t0 = fmaxf(sv[0], sv[2]), t1 = fmaxf(sv[1], sv[3]);
#pragma unroll
            for (int off = 4; off < 32; off <<= 1) {
                t0 = fmaxf(t0, __shfl_xor_sync(0xffffffffu, t0, off));
                t1 = fmaxf(t1, __shfl_xor_sync(0xffffffffu, t1, off));
            }
            const float n0 = fmaxf(m0, t0), n1 = fmaxf(m1, t1);
            if (__any_sync(0xffffffffu, (n0 != m0) || (n1 != m1))) {
                const float a0 = ex2((m0 - n0) * LOG2E), a1 = ex2((m1 - n1) * LOG2E);
                l0 *= a0; l1 *= a1;
#pragma unroll
                for (int i = 0; i < 8; i++) { o[i][0] *= a0; o[i][1] *= a1; o[i][2] *= a0; o[i][3] *= a1; }
                m0 = n0; m1 = n1;
            }
            const float p0 = ex2((sv[0] - m0) * LOG2E), p1 = ex2((sv[1] - m1) * LOG2E);
            const float p2 = ex2((sv[2] - m0) * LOG2E), p3 = ex2((sv[3] - m1) * LOG2E);
            l0 += p0 + p2; l1 += p1 + p3;
            const uint32_t b0 = movmat(pack_bf16(p0, p1)), b1 = movmat(pack_bf16(p2, p3));
            mbar_wait(bar_full + slot * 8 + 8, ph);
#pragma unroll
            for (int mt = 0; mt < 8; mt++) {
                uint32_t a[4];
                ldsm4t(a, vb + (mt >> 2) * 8192 + voff + ((((mt & 3) * 2 + vc) ^ vx) << 4));
                mma16816(o[mt], a, b0, b1);
            }
            __syncwarp();
            if (lane == 0) mbar_arrive(bar_empty + slot * 8 + 8);
            slot += 4;
            if (slot >= NSLOT) { slot -= NSLOT; ph ^= 1; }
        }
    }
    STAMP(4);
    {
        float* s_mrg = reinterpret_cast<float*>(sptr + OFF_MRG);
        float* s_ml = reinterpret_cast<float*>(sptr + OFF_ML);
#pragma unroll
        for (int off = 4; off < 32; off <<= 1) {
            l0 += __shfl_xor_sync(0xffffffffu, l0, off);
            l1 += __shfl_xor_sync(0xffffffffu, l1, off);
        }
        if (t < 2) {
            float* p0 = s_mrg + (warp * 4 + 2 * t) * 132 + g;
#pragma unroll
            for (int mt = 0; mt < 8; mt++) {
                p0[mt * 16] = o[mt][0];
                p0[132 + mt * 16] = o[mt][1];
                p0[mt * 16 + 8] = o[mt][2];
                p0[132 + mt * 16 + 8] = o[mt][3];
            }
            if (g == 0) *reinterpret_cast<float4*>(s_ml + (warp * 4 + 2 * t) * 2) = make_float4(m0, l0, m1, l1);
        }
        bar_sync(5, 256);
        const int hd = tid >> 6, dp = tid & 63;
        float mw[8], lw[8], M = -INFINITY;
#pragma unroll
        for (int w = 0; w < 8; w++) {
            float2 v = *reinterpret_cast<const float2*>(s_ml + (w * 4 + hd) * 2);
            mw[w] = v.x; lw[w] = v.y;
            M = fmaxf(M, v.x);
        }
        float a0 = 0.f, a1 = 0.f, L = 0.f;
#pragma unroll
        for (int w = 0; w < 8; w++) {
            const float f = ex2((mw[w] - M) * LOG2E);
            float2 v = *reinterpret_cast<const float2*>(s_mrg + (w * 4 + hd) * 132 + 2 * dp);
            a0 = fmaf(f, v.x, a0); a1 = fmaf(f, v.y, a1); L = fmaf(f, lw[w], L);
        }
        const int rec = ((kvh * 4 + hd) * NB + ab) * 4 + split;
        stx64(&g_scr.po[rec * DH + 2 * dp], nzf(a0), nzf(a1));
        if (dp == 0) stx64(&g_scr.pml[rec * 2], nzf(M), nzf(L));
    }
    STAMP(5);
    {
        const int hh = cta >> 2;
        const int b = tid >> 6, d8 = (tid >> 2) & 15, sp = tid & 3;
        const int rec = (hh * NB + b) * 4 + sp;
        const uint32_t* op = g_scr.po + rec * DH + d8 * 8;
        const uint32_t* mp = g_scr.pml + rec * 2;
        uint4 v0, v1;
        uint2 ml;
        unsigned it = 0;
        bool ok;
        do {
            v0 = ldx128(op);
            v1 = ldx128(op + 4);
            ml = ldx64(mp);
            ok = ok4(v0) && ok4(v1) && ok2(ml);
        } while (!ok && ++it < SPIN_LIMIT);
        __syncwarp();
        const float ms = __uint_as_float(ml.x);
        float M = fmaxf(ms, __shfl_xor_sync(0xffffffffu, ms, 1));
        M = fmaxf(M, __shfl_xor_sync(0xffffffffu, M, 2));
        const float f = ex2((ms - M) * LOG2E);
        float L = f * __uint_as_float(ml.y);
        L += __shfl_xor_sync(0xffffffffu, L, 1);
        L += __shfl_xor_sync(0xffffffffu, L, 2);
        const float fw = __fdiv_rn(f, L);
        float a[8] = {fw * __uint_as_float(v0.x), fw * __uint_as_float(v0.y), fw * __uint_as_float(v0.z), fw * __uint_as_float(v0.w),
                      fw * __uint_as_float(v1.x), fw * __uint_as_float(v1.y), fw * __uint_as_float(v1.z), fw * __uint_as_float(v1.w)};
        bfly<8>(a, lane, 2);
        bfly<4>(a, lane, 1);
        *reinterpret_cast<uint32_t*>(sptr + OFF_SO + b * 272 + (d8 * 8 + sp * 2) * 2) = pack_bf16(a[0], a[1]);
        STAMP(6);
        constexpr int S0 = NKV % NSLOT, P0 = (NKV / NSLOT) & 1;
        static_assert(S0 + 4 < NSLOT, "tail items must not wrap");
        const int half = warp >> 2;
        mbar_wait(bar_full + (S0 + half) * 8, P0);
        uint32_t af[8][4];
        {
            const uint32_t wb = sbase + (S0 + half) * SLOT;
            const int krow = (lane & 7) + (lane >> 4) * 8;
            const uint32_t ch = (warp & 3) * 2 + ((lane >> 3) & 1);
#pragma unroll
            for (int ks = 0; ks < 8; ks++) ldsm4t(af[ks], wb + (ks * 16 + krow) * 128 + ((ch ^ (krow & 7)) << 4));
        }
        bar_sync(5, 256);
        float d[2][4] = {{0.f, 0.f, 0.f, 0.f}, {0.f, 0.f, 0.f, 0.f}};
#pragma unroll
        for (int kp = 0; kp < 4; kp++) {
            uint32_t bf[4];
            ldsm4(bf, sbase + OFF_SO + (lane & 3) * 272 + kp * 64 + (lane >> 3) * 16);
            mma16816(d[0], af[2 * kp], bf[0], bf[1]);
            mma16816(d[1], af[2 * kp + 1], bf[2], bf[3]);
        }
        if (t < 2) {
            uint32_t* p = g_scr.wop + (hh * NB + 2 * t) * DM + (cta & 3) * 128 + warp * 16 + g;
            stx32(p, nzf(d[0][0] + d[1][0]));
            stx32(p + DM, nzf(d[0][1] + d[1][1]));
            stx32(p + 8, nzf(d[0][2] + d[1][2]));
            stx32(p + DM + 8, nzf(d[0][3] + d[1][3]));
        }
    }
    STAMP(7);
    if (warp < 4) {
        const uint32_t* p = g_scr.wop + (lane * NB + warp) * DM + cta * 4;
        uint4 v;
        unsigned it = 0;
        do { v = ldx128(p); } while (!ok4(v) && ++it < SPIN_LIMIT);
        __syncwarp();
        float a[4] = {__uint_as_float(v.x), __uint_as_float(v.y), __uint_as_float(v.z), __uint_as_float(v.w)};
        bfly<4>(a, lane, 16);
        bfly<2>(a, lane, 8);
        float s = a[0];
        s += __shfl_xor_sync(0xffffffffu, s, 4);
        s += __shfl_xor_sync(0xffffffffu, s, 2);
        s += __shfl_xor_sync(0xffffffffu, s, 1);
        const int col = lane >> 3;
        const float x1 = rbf(s_loc[32 + warp * 4 + col] + rbf(s_loc[warp * 4 + col] * rbf(s)));
        const float c1 = __shfl_sync(0xffffffffu, x1, 8), c2 = __shfl_sync(0xffffffffu, x1, 16), c3 = __shfl_sync(0xffffffffu, x1, 24);
        if (lane == 0) stx64(&g_scr.x1[warp * 256 + cta * 2], nz(pack_bf16(x1, c1)), nz(pack_bf16(c2, c3)));
        if ((lane & 7) == 0) s_loc[48 + warp * 4 + col] = x1;
    }
    STAMP(8);
    if (cta < NFFN) {
        constexpr int S0 = NKV % NSLOT + 2, P0 = (NKV / NSLOT) & 1;
        {
            const int b = warp & 3, hf = warp >> 2;
            const uint32_t* p = g_scr.x1 + b * 256 + lane * 4;
            uint4 v0, v1;
            unsigned it = 0;
            do { v0 = ldx128(p); v1 = ldx128(p + 128); } while (!(ok4(v0) && ok4(v1)) && ++it < SPIN_LIMIT);
            __syncwarp();
            float v[16], mb, sd;
            unpack8(v0, v);
            unpack8(v1, v + 8);
            ln_stats(v, mb, sd);
            float sbf[8], cbf[8], r[8];
            unpack8(sbv, sbf);
            unpack8(cbv, cbf);
#pragma unroll
            for (int i = 0; i < 8; i++) r[i] = ln_mod(hf ? v[8 + i] : v[i], mb, sd, cbf[i], sbf[i]);
            *reinterpret_cast<uint4*>(sptr + OFF_H2 + b * 1040 + hf * 512 + lane * 16) =
                make_uint4(pack_bf16(r[0], r[1]), pack_bf16(r[2], r[3]), pack_bf16(r[4], r[5]), pack_bf16(r[6], r[7]));
        }
        STAMP(9);
        if (tid < 8) g_h[cta * 8 + tid] = 0;
        if (cta < NCTA - NFFN && tid >= 8 && tid < 16) g_h[(NFFN + cta) * 8 + tid - 8] = 0;
        uint32_t ag[4][4], au[4][4];
        {
            mbar_wait(bar_full + S0 * 8, P0);
            mbar_wait(bar_full + (S0 + 1) * 8, P0);
            const int krow = warp * 64 + (lane & 7) + (lane >> 4) * 8;
            const uint32_t ch = (lane >> 3) & 1;
#pragma unroll
            for (int ks = 0; ks < 4; ks++) {
                const int r = krow + ks * 16;
                const uint32_t off = r * 32 + ((ch ^ ((r >> 2) & 1)) << 4);
                ldsm4t(ag[ks], sbase + S0 * SLOT + off);
                ldsm4t(au[ks], sbase + (S0 + 1) * SLOT + off);
            }
        }
        bar_sync(5, 256);
        {
            float dg[4] = {0.f, 0.f, 0.f, 0.f}, du[4] = {0.f, 0.f, 0.f, 0.f};
#pragma unroll
            for (int kp = 0; kp < 2; kp++) {
                uint32_t bf[4];
                ldsm4(bf, sbase + OFF_H2 + (lane & 3) * 1040 + warp * 128 + kp * 64 + (lane >> 3) * 16);
                mma16816(dg, ag[2 * kp], bf[0], bf[1]);
                mma16816(du, au[2 * kp], bf[0], bf[1]);
                mma16816(dg, ag[2 * kp + 1], bf[2], bf[3]);
                mma16816(du, au[2 * kp + 1], bf[2], bf[3]);
            }
            if (t < 2) {
                float* p = s_red + warp * 128 + g * 8 + t * 4;
                *reinterpret_cast<float4*>(p) = make_float4(dg[0], du[0], dg[1], du[1]);
                *reinterpret_cast<float4*>(p + 64) = make_float4(dg[2], du[2], dg[3], du[3]);
            }
        }
        uint32_t ad[4][4];
        {
            mbar_wait(bar_full + (S0 + 2) * 8, P0);
            const int krow = (lane & 7) + (lane >> 4) * 8;
#pragma unroll
            for (int mt = 0; mt < 4; mt++) {
                const uint32_t ch = mt * 2 + ((lane >> 3) & 1);
                ldsm4t(ad[mt], sbase + (S0 + 2) * SLOT + warp * 2048 + krow * 128 + ((ch ^ (krow & 7)) << 4));
            }
        }
        bar_sync(5, 256);
        if (tid < 64) {
            float gsum = 0.f, usum = 0.f;
#pragma unroll
            for (int w = 0; w < 8; w++) {
                float2 v = *reinterpret_cast<const float2*>(s_red + w * 128 + tid * 2);
                gsum += v.x; usum += v.y;
            }
            const float gv = rbf(gsum), uv = rbf(usum);
            const float inner = 0.7978845608028654f * (gv + 0.044715f * gv * gv * gv);
            const float ge = rbf(0.5f * gv * (1.0f + tanhf(inner)));
            const int col = tid >> 2, b = tid & 3;
            *reinterpret_cast<bf16*>(sptr + OFF_ACT + b * 48 + col * 2) = __float2bfloat16_rn(ge * uv);
        }
        bar_sync(5, 256);
        {
            uint32_t bf[2];
            ldsm2(bf, sbase + OFF_ACT + (lane & 3) * 48 + ((lane >> 3) & 1) * 16);
            uint32_t* p = g_scr.dnp + ((size_t)cta * DM + warp * 64 + g) * NB + 2 * t;
#pragma unroll
            for (int mt = 0; mt < 4; mt++) {
                float d[4] = {0.f, 0.f, 0.f, 0.f};
                mma16816(d, ad[mt], bf[0], bf[1]);
                if (t < 2) {
                    stx64(p + mt * 64, nzf(d[0]), nzf(d[1]));
                    stx64(p + mt * 64 + 32, nzf(d[2]), nzf(d[3]));
                }
            }
        }
    }
    STAMP(10);
    {
        const int pr = tid >> 2, col = tid & 3;
        const uint32_t* p0 = g_scr.dnp + ((size_t)pr * DM + cta * 4 + col) * NB;
        const uint32_t* p1 = p0 + (size_t)64 * DM * NB;
        const bool two = pr + 64 < NFFN;
        uint4 v0, v1 = make_uint4(0x80000000u, 0x80000000u, 0x80000000u, 0x80000000u);
        unsigned it = 0;
        do {
            v0 = ldx128(p0);
            if (two) v1 = ldx128(p1);
        } while (!(ok4(v0) && ok4(v1)) && ++it < SPIN_LIMIT);
        __syncwarp();
        float a[4] = {__uint_as_float(v0.x) + __uint_as_float(v1.x), __uint_as_float(v0.y) + __uint_as_float(v1.y),
                      __uint_as_float(v0.z) + __uint_as_float(v1.z), __uint_as_float(v0.w) + __uint_as_float(v1.w)};
        bfly<4>(a, lane, 16);
        bfly<2>(a, lane, 8);
        float s = a[0] + __shfl_xor_sync(0xffffffffu, a[0], 4);
        if (!(lane & 4)) s_red2[warp * 16 + (lane >> 3) * 4 + col] = s;
        bar_sync(5, 256);
        if (tid < 16) {
            float f = 0.f;
#pragma unroll
            for (int w = 0; w < 8; w++) f += s_red2[w * 16 + tid];
            const float r = s_loc[48 + tid] + rbf(s_loc[16 + tid] * rbf(f));
            out[(tid >> 2) * DM + cta * 4 + (tid & 3)] = __float2bfloat16_rn(r);
        }
    }
    STAMP(11);
}

typedef CUresult (*EncodeFn)(CUtensorMap*, CUtensorMapDataType, cuuint32_t, void*, const cuuint64_t*, const cuuint64_t*,
                             const cuuint32_t*, const cuuint32_t*, CUtensorMapInterleave, CUtensorMapSwizzle,
                             CUtensorMapL2promotion, CUtensorMapFloatOOBfill);

void encode(EncodeFn fn, CUtensorMap* m, const void* base, int rank, const cuuint64_t* dims, const cuuint64_t* strides,
            const cuuint32_t* box, CUtensorMapSwizzle sw, CUtensorMapL2promotion promo) {
    cuuint32_t es[3] = {1, 1, 1};
    fn(m, CU_TENSOR_MAP_DATA_TYPE_BFLOAT16, rank, const_cast<void*>(base), dims, strides, box, es,
       CU_TENSOR_MAP_INTERLEAVE_NONE, sw, promo, CU_TENSOR_MAP_FLOAT_OOB_FILL_NONE);
}

}

extern "C" void kernel_launch(void* const* d_in, const int* in_sizes, int n_in, void* d_out, int out_size) {
    (void)in_sizes; (void)n_in; (void)out_size;
    const bf16* x = (const bf16*)d_in[0];
    const bf16* kc = (const bf16*)d_in[1];
    const bf16* vc = (const bf16*)d_in[2];
    const bf16* wq = (const bf16*)d_in[3];
    const bf16* wo = (const bf16*)d_in[4];
    const bf16* wg = (const bf16*)d_in[6];
    const bf16* wu = (const bf16*)d_in[7];
    const bf16* wd = (const bf16*)d_in[8];
    const bf16* cv = (const bf16*)d_in[9];
    const bf16* wm = (const bf16*)d_in[10];

    static EncodeFn fn = nullptr;
    if (!fn) {
        void* p = nullptr;
        cudaDriverEntryPointQueryResult st;
        cudaGetDriverEntryPoint("cuTensorMapEncodeTiled", &p, cudaEnableDefault, &st);
        fn = (EncodeFn)p;
        cudaFuncSetAttribute(fused_kernel, cudaFuncAttributeMaxDynamicSharedMemorySize, SMEM_BYTES);
    }
    CUtensorMap tmK, tmV, tmWo, tmG, tmU, tmD;
    {
        cuuint64_t dims[3] = {64, (cuuint64_t)NB * HKV * SK, 2};
        cuuint64_t strides[2] = {256, 128};
        cuuint32_t box[3] = {64, TK, 2};
        encode(fn, &tmK, kc, 3, dims, strides, box, CU_TENSOR_MAP_SWIZZLE_128B, CU_TENSOR_MAP_L2_PROMOTION_L2_256B);
        encode(fn, &tmV, vc, 3, dims, strides, box, CU_TENSOR_MAP_SWIZZLE_128B, CU_TENSOR_MAP_L2_PROMOTION_L2_256B);
    }
    {
        cuuint64_t dims[2] = {DM, HQ * DH};
        cuuint64_t strides[1] = {DM * 2};
        cuuint32_t box[2] = {64, 128};
        encode(fn, &tmWo, wo, 2, dims, strides, box, CU_TENSOR_MAP_SWIZZLE_128B, CU_TENSOR_MAP_L2_PROMOTION_L2_256B);
    }
    {
        cuuint64_t dims[2] = {FF, DM};
        cuuint64_t strides[1] = {FF * 2};
        cuuint32_t box[2] = {16, 256};
        encode(fn, &tmG, wg, 2, dims, strides, box, CU_TENSOR_MAP_SWIZZLE_32B, CU_TENSOR_MAP_L2_PROMOTION_L2_128B);
        encode(fn, &tmU, wu, 2, dims, strides, box, CU_TENSOR_MAP_SWIZZLE_32B, CU_TENSOR_MAP_L2_PROMOTION_L2_128B);
    }
    {
        cuuint64_t dims[3] = {64, FF, 8};
        cuuint64_t strides[2] = {DM * 2, 128};
        cuuint32_t box[3] = {64, 16, 8};
        encode(fn, &tmD, wd, 3, dims, strides, box, CU_TENSOR_MAP_SWIZZLE_128B, CU_TENSOR_MAP_L2_PROMOTION_L2_256B);
    }
    fused_kernel<<<NCTA, NTHREADS, SMEM_BYTES>>>(tmK, tmV, tmWo, tmG, tmU, tmD, x, wq, cv, wm, (bf16*)d_out);
}
```

```cpp
#include <cuda_runtime.h>
#include <cuda_bf16.h>
#include <cuda.h>
#include <stdint.h>

typedef __nv_bfloat16 bf16;

namespace {

constexpr int NB = 4, DM = 512, HQ = 32, HKV = 8, SK = 8192, DH = 128, FF = 1792;
constexpr int NCTA = 128;
constexpr int NSLOT = 12;
constexpr int SLOT = 16384;
constexpr int TK = 64;
constexpr int NTILE = 32;
constexpr int IT_KV = 4;
constexpr int IT_WO = IT_KV + 2 * NTILE;
constexpr int INFLIGHT = 4;
constexpr int NFFN = FF / 16;
constexpr int NREP = 8;
constexpr int NTHREADS = 320;
constexpr unsigned SPIN_LIMIT = 1u << 22;
constexpr float LOG2E = 1.4426950408889634f;

struct __align__(128) Scratch {
    uint32_t q[NB * HQ * 64];
    uint32_t sbcb[2 * 64 * 16];
    uint32_t po[HQ * NB * 4 * DH];
    uint32_t pml[HQ * NB * 4 * 2];
    uint32_t wop[64 * HQ * 32];
    uint32_t x1[NREP * 64 * 16];
    uint32_t dnp[64 * NFFN * 32];
};
static_assert(sizeof(Scratch) % (64 * 16) == 0, "scratch must split evenly");
__device__ Scratch g_scr;
__device__ __align__(128) uint32_t g_h[NREP * 64 * 16];
#define STAMP(i) do {} while (0)

constexpr int OFF_MRG = NSLOT * SLOT;
constexpr int OFF_ML = OFF_MRG + 8 * 4 * 132 * 4;
constexpr int OFF_RED = OFF_ML + 8 * 4 * 2 * 4;
constexpr int OFF_RED2 = OFF_RED + 8 * 128 * 4;
constexpr int OFF_SO = OFF_RED2 + 8 * 96 * 4;
constexpr int OFF_ST = OFF_SO + 4 * 136 * 2;
constexpr int OFF_ACT = OFF_ST + 8 * 4 * 8;
constexpr int OFF_LOC = OFF_ACT + 4 * 24 * 2;
constexpr int OFF_BAR = OFF_LOC + 64 * 4;
constexpr int SMEM_USED = OFF_BAR + 2 * NSLOT * 8;
constexpr int SMEM_BYTES = SMEM_USED + 1024;
static_assert(SMEM_BYTES <= 232448, "too much smem");
static_assert(OFF_BAR % 8 == 0 && OFF_SO % 16 == 0 && OFF_ST % 16 == 0 && OFF_ACT % 16 == 0, "align");
__host__ __device__ constexpr int slot_of(int item) { return item % NSLOT; }
__host__ __device__ constexpr int phase_of(int item) { return (item / NSLOT) & 1; }

__device__ __forceinline__ uint32_t smem_u32(const void* p) { return (uint32_t)__cvta_generic_to_shared(p); }
__device__ __forceinline__ void mbar_init(uint32_t bar, int cnt) { asm volatile("mbarrier.init.shared::cta.b64 [%0], %1;" ::"r"(bar), "r"(cnt) : "memory"); }
__device__ __forceinline__ void mbar_expect_tx(uint32_t bar, uint32_t bytes) { asm volatile("mbarrier.arrive.expect_tx.shared::cta.b64 _, [%0], %1;" ::"r"(bar), "r"(bytes) : "memory"); }
__device__ __forceinline__ void mbar_arrive(uint32_t bar) { asm volatile("mbarrier.arrive.shared::cta.b64 _, [%0];" ::"r"(bar) : "memory"); }
__device__ __forceinline__ bool mbar_try(uint32_t bar, uint32_t parity) {
    uint32_t ok;
    asm volatile("{\n.reg .pred p;\nmbarrier.try_wait.parity.shared::cta.b64 p, [%1], %2;\nselp.u32 %0, 1, 0, p;\n}" : "=r"(ok) : "r"(bar), "r"(parity) : "memory");
    return ok != 0;
}
__device__ __forceinline__ void mbar_wait(uint32_t bar, uint32_t parity) {
    unsigned it = 0;
    while (!mbar_try(bar, parity)) { if (++it > SPIN_LIMIT) break; }
}
__device__ __forceinline__ void tma2d(uint32_t dst, const CUtensorMap* m, int c0, int c1, uint32_t bar) {
    asm volatile("cp.async.bulk.tensor.2d.shared::cluster.global.mbarrier::complete_tx::bytes [%0], [%1, {%3, %4}], [%2];" ::"r"(dst), "l"(m), "r"(bar), "r"(c0), "r"(c1) : "memory");
}
__device__ __forceinline__ void tma3d(uint32_t dst, const CUtensorMap* m, int c0, int c1, int c2, uint32_t bar) {
    asm volatile("cp.async.bulk.tensor.3d.shared::cluster.global.mbarrier::complete_tx::bytes [%0], [%1, {%3, %4, %5}], [%2];" ::"r"(dst), "l"(m), "r"(bar), "r"(c0), "r"(c1), "r"(c2) : "memory");
}
__device__ __forceinline__ void tma3d_hint(uint32_t dst, const CUtensorMap* m, int c0, int c1, int c2, uint32_t bar, uint64_t pol) {
    asm volatile("cp.async.bulk.tensor.3d.shared::cluster.global.mbarrier::complete_tx::bytes.L2::cache_hint [%0], [%1, {%3, %4, %5}], [%2], %6;" ::"r"(dst), "l"(m), "r"(bar), "r"(c0), "r"(c1), "r"(c2), "l"(pol) : "memory");
}
__device__ __forceinline__ void bar_sync(int id, int n) { asm volatile("bar.sync %0, %1;" ::"r"(id), "r"(n) : "memory"); }
__device__ __forceinline__ void bar_arrive(int id, int n) { asm volatile("bar.arrive %0, %1;" ::"r"(id), "r"(n) : "memory"); }
__device__ __forceinline__ void ldsm4(uint32_t* r, uint32_t addr) {
    asm volatile("ldmatrix.sync.aligned.m8n8.x4.shared.b16 {%0,%1,%2,%3}, [%4];" : "=r"(r[0]), "=r"(r[1]), "=r"(r[2]), "=r"(r[3]) : "r"(addr) : "memory");
}
__device__ __forceinline__ void ldsm4t(uint32_t* r, uint32_t addr) {
    asm volatile("ldmatrix.sync.aligned.m8n8.x4.trans.shared.b16 {%0,%1,%2,%3}, [%4];" : "=r"(r[0]), "=r"(r[1]), "=r"(r[2]), "=r"(r[3]) : "r"(addr) : "memory");
}
__device__ __forceinline__ void ldsm2(uint32_t* r, uint32_t addr) {
    asm volatile("ldmatrix.sync.aligned.m8n8.x2.shared.b16 {%0,%1}, [%2];" : "=r"(r[0]), "=r"(r[1]) : "r"(addr) : "memory");
}
__device__ __forceinline__ void mma16816(float* d, const uint32_t* a, uint32_t b0, uint32_t b1) {
    asm volatile("mma.sync.aligned.m16n8k16.row.col.f32.bf16.bf16.f32 {%0,%1,%2,%3}, {%4,%5,%6,%7}, {%8,%9}, {%0,%1,%2,%3};"
                 : "+f"(d[0]), "+f"(d[1]), "+f"(d[2]), "+f"(d[3]) : "r"(a[0]), "r"(a[1]), "r"(a[2]), "r"(a[3]), "r"(b0), "r"(b1));
}
__device__ __forceinline__ uint32_t movmat(uint32_t a) {
    uint32_t d;
    asm volatile("movmatrix.sync.aligned.m8n8.trans.b16 %0, %1;" : "=r"(d) : "r"(a));
    return d;
}
__device__ __forceinline__ uint32_t pack_bf16(float lo, float hi) {
    uint32_t r;
    asm("cvt.rn.bf16x2.f32 %0, %1, %2;" : "=r"(r) : "f"(hi), "f"(lo));
    return r;
}
__device__ __forceinline__ float rbf(float x) { return __bfloat162float(__float2bfloat16_rn(x)); }
__device__ __forceinline__ float bf_lo(uint32_t w) { return __uint_as_float(w << 16); }
__device__ __forceinline__ float bf_hi(uint32_t w) { return __uint_as_float(w & 0xffff0000u); }
__device__ __forceinline__ float ex2(float x) { float y; asm("ex2.approx.ftz.f32 %0, %1;" : "=f"(y) : "f"(x)); return y; }
__device__ __forceinline__ uint32_t nz(uint32_t w) { return w ? w : 0x80000000u; }
__device__ __forceinline__ uint32_t nzf(float f) { return nz(__float_as_uint(f)); }
__device__ __forceinline__ uint2 ldg64(const void* p) {
    uint2 v;
    asm volatile("ld.global.nc.L1::no_allocate.v2.u32 {%0,%1}, [%2];" : "=r"(v.x), "=r"(v.y) : "l"(p));
    return v;
}
__device__ __forceinline__ uint4 ldg128(const void* p) {
    uint4 v;
    asm volatile("ld.global.nc.L1::no_allocate.v4.u32 {%0,%1,%2,%3}, [%4];" : "=r"(v.x), "=r"(v.y), "=r"(v.z), "=r"(v.w) : "l"(p));
    return v;
}
__device__ __forceinline__ uint4 ldx128(const void* p) {
    uint4 v;
    asm volatile("ld.relaxed.gpu.global.v4.u32 {%0,%1,%2,%3}, [%4];" : "=r"(v.x), "=r"(v.y), "=r"(v.z), "=r"(v.w) : "l"(p) : "memory");
    return v;
}
__device__ __forceinline__ uint2 ldx64(const void* p) {
    uint2 v;
    asm volatile("ld.relaxed.gpu.global.v2.u32 {%0,%1}, [%2];" : "=r"(v.x), "=r"(v.y) : "l"(p) : "memory");
    return v;
}
__device__ __forceinline__ void stx32(void* p, uint32_t v) { asm volatile("st.relaxed.gpu.global.u32 [%0], %1;" ::"l"(p), "r"(v) : "memory"); }
__device__ __forceinline__ void stx64(void* p, uint32_t a, uint32_t b) { asm volatile("st.relaxed.gpu.global.v2.u32 [%0], {%1,%2};" ::"l"(p), "r"(a), "r"(b) : "memory"); }
__device__ __forceinline__ bool ok4(const uint4& v) { return v.x && v.y && v.z && v.w; }
__device__ __forceinline__ bool ok2(const uint2& v) { return v.x && v.y; }

template <int N>
__device__ __forceinline__ void bfly(float* a, int lane, int off) {
    const bool up = (lane & off) != 0;
#pragma unroll
    for (int i = 0; i < N / 2; i++) {
        float send = up ? a[i] : a[i + N / 2];
        float keep = up ? a[i + N / 2] : a[i];
        a[i] = keep + __shfl_xor_sync(0xffffffffu, send, off);
    }
}
__device__ __forceinline__ float warp_sum(float v) {
#pragma unroll
    for (int o = 16; o; o >>= 1) v += __shfl_xor_sync(0xffffffffu, v, o);
    return v;
}
__device__ __forceinline__ void ln_stats(const float* v, float& mean_b, float& sd_b) {
    float s = 0.f;
#pragma unroll
    for (int i = 0; i < 16; i++) s += v[i];
    float mean = warp_sum(s) * (1.0f / DM);
    float q = 0.f;
#pragma unroll
    for (int i = 0; i < 16; i++) { float d = v[i] - mean; q += d * d; }
    float var = warp_sum(q) * (1.0f / DM);
    mean_b = rbf(mean);
    sd_b = rbf(sqrtf(rbf(rbf(var) + 1e-5f)));
}
__device__ __forceinline__ float ln_mod(float x, float mean_b, float sd_b, float one_plus_c, float sh) {
    float n = rbf(__fdiv_rn(rbf(x - mean_b), sd_b));
    return rbf(rbf(n * one_plus_c) + sh);
}
__device__ __forceinline__ void unpack8(const uint4& v, float* f) {
    f[0] = bf_lo(v.x); f[1] = bf_hi(v.x); f[2] = bf_lo(v.y); f[3] = bf_hi(v.y);
    f[4] = bf_lo(v.z); f[5] = bf_hi(v.z); f[6] = bf_lo(v.w); f[7] = bf_hi(v.w);
}

__device__ __forceinline__ void ldsm2t(uint32_t& r0, uint32_t& r1, uint32_t addr) {
    asm volatile("ldmatrix.sync.aligned.m8n8.x2.trans.shared.b16 {%0,%1}, [%2];" : "=r"(r0), "=r"(r1) : "r"(addr) : "memory");
}
__device__ __forceinline__ void stx128(void* p, uint4 v) {
    asm volatile("st.relaxed.gpu.global.v4.u32 [%0], {%1,%2,%3,%4};" ::"l"(p), "r"(v.x), "r"(v.y), "r"(v.z), "r"(v.w) : "memory");
}
__device__ __forceinline__ uint32_t ldx32(const void* p) {
    uint32_t v;
    asm volatile("ld.relaxed.gpu.global.u32 %0, [%1];" : "=r"(v) : "l"(p) : "memory");
    return v;
}
__device__ __forceinline__ uint4 make_record(float v, int lane, int grp) {
    const float vn = __shfl_down_sync(0xffffffffu, v, 1);
    const uint32_t w = nz(pack_bf16(v, vn));
    const int src = (lane & 3) * 8;
    uint4 r;
    r.x = __shfl_sync(0xffffffffu, w, src + 2 * ((0 + grp) & 3));
    r.y = __shfl_sync(0xffffffffu, w, src + 2 * ((1 + grp) & 3));
    r.z = __shfl_sync(0xffffffffu, w, src + 2 * ((2 + grp) & 3));
    r.w = __shfl_sync(0xffffffffu, w, src + 2 * ((3 + grp) & 3));
    return r;
}
__device__ __forceinline__ void fold_halves(const float* d0, const float* d1, int t, float* r) {
#pragma unroll
    for (int i = 0; i < 4; i++) {
        const float v = (t < 2) ? d0[i] : d1[i];
        r[i] = v + __shfl_xor_sync(0xffffffffu, v, 2);
    }
}

__global__ void __launch_bounds__(NTHREADS, 1)
fused_kernel(const __grid_constant__ CUtensorMap tmK, const __grid_constant__ CUtensorMap tmV,
             const __grid_constant__ CUtensorMap tmM, const __grid_constant__ CUtensorMap tmQ,
             const __grid_constant__ CUtensorMap tmWo, const __grid_constant__ CUtensorMap tmG,
             const __grid_constant__ CUtensorMap tmU, const __grid_constant__ CUtensorMap tmD,
             const bf16* __restrict__ x, const bf16* __restrict__ cvec, bf16* __restrict__ out) {
    extern __shared__ uint8_t smem_raw[];
    const uint32_t sbase = (smem_u32(smem_raw) + 1023u) & ~1023u;
    uint8_t* sptr = smem_raw + (sbase - smem_u32(smem_raw));
    const int tid = threadIdx.x, lane = tid & 31, warp = tid >> 5;
    const int cta = blockIdx.x;
    const int odd = cta & 1, cgrp = cta >> 1;
    const uint32_t bar_full = sbase + OFF_BAR, bar_empty = bar_full + NSLOT * 8;

    if (warp == 8) {
        uint64_t pol;
        asm volatile("createpolicy.fractional.L2::evict_first.b64 %0, 1.0;" : "=l"(pol));
        const int row0 = cta * (NTILE * TK);
        if (lane == 0) {
#pragma unroll
            for (int i = 0; i < 8; i++) mbar_init(bar_full + i * 8, 1);
            asm volatile("fence.mbarrier_init.release.cluster;" ::: "memory");
            const int mcol = odd * (3 * DM) + cgrp * 8;
            if (!odd) {
                mbar_expect_tx(bar_full, SLOT);
#pragma unroll
                for (int i = 0; i < 4; i++) tma2d(sbase + i * 4096, &tmM, mcol + (i >> 1) * DM, (i & 1) * 256, bar_full);
            }
#pragma unroll
            for (int i = 1; i < 3; i++) {
                mbar_expect_tx(bar_full + i * 8, SLOT);
                tma2d(sbase + i * SLOT, &tmQ, cta * 32, (i - 1) * 256, bar_full + i * 8);
            }
#pragma unroll
            for (int i = 0; i < 4; i++) {
                mbar_expect_tx(bar_full + (IT_KV + i) * 8, SLOT);
                tma3d_hint(sbase + (IT_KV + i) * SLOT, (i & 1) ? &tmV : &tmK, 0, row0 + (i >> 1) * TK, 0, bar_full + (IT_KV + i) * 8, pol);
            }
            if (odd) {
                mbar_expect_tx(bar_full, SLOT);
#pragma unroll
                for (int i = 0; i < 4; i++) tma2d(sbase + i * 4096, &tmM, mcol + (i >> 1) * DM, (i & 1) * 256, bar_full);
            }
            mbar_expect_tx(bar_full + 3 * 8, 8192);
            tma2d(sbase + 3 * SLOT, &tmM, mcol + 2 * DM, 0, bar_full + 3 * 8);
            tma2d(sbase + 3 * SLOT + 4096, &tmM, mcol + 2 * DM, 256, bar_full + 3 * 8);
            for (int i = 8; i < NSLOT; i++) mbar_init(bar_full + i * 8, 1);
            for (int i = 0; i < NSLOT; i++) mbar_init(bar_empty + i * 8, 4);
            asm volatile("fence.mbarrier_init.release.cluster;" ::: "memory");
        }
        __syncwarp();
        bar_arrive(3, 288);
        if (lane == 0) {
            asm volatile("prefetch.tensormap [%0];" ::"l"(&tmWo) : "memory");
            asm volatile("prefetch.tensormap [%0];" ::"l"(&tmG) : "memory");
            asm volatile("prefetch.tensormap [%0];" ::"l"(&tmU) : "memory");
            asm volatile("prefetch.tensormap [%0];" ::"l"(&tmD) : "memory");
            const int nitems = IT_WO + ((cta < NFFN) ? 5 : 2);
            int slot = 8, ph = 0;
            int wslot = 8 - INFLIGHT, wph = 0;
            for (int i = 8; i < nitems; i++) {
                mbar_wait(bar_full + wslot * 8, wph);
                mbar_wait(bar_empty + slot * 8, ph ^ 1);
                const uint32_t dst = sbase + slot * SLOT, fb = bar_full + slot * 8;
                mbar_expect_tx(fb, SLOT);
                if (i < IT_WO) {
                    tma3d_hint(dst, (i & 1) ? &tmV : &tmK, 0, row0 + ((i - IT_KV) >> 1) * TK, 0, fb, pol);
                } else if (i < IT_WO + 2) {
                    tma2d(dst, &tmWo, (cta & 3) * 128 + (i - IT_WO) * 64, (cta >> 2) * 128, fb);
                } else if (i < IT_WO + 4) {
                    const CUtensorMap* m = (i == IT_WO + 2) ? &tmG : &tmU;
                    tma2d(dst, m, cta * 16, 0, fb);
                    tma2d(dst + 8192, m, cta * 16, 256, fb);
                } else {
                    tma3d(dst, &tmD, 0, cta * 16, 0, fb);
                }
                if (++slot == NSLOT) { slot = 0; ph ^= 1; }
                if (++wslot == NSLOT) { wslot = 0; wph ^= 1; }
            }
        }
        return;
    }

    float* s_red = reinterpret_cast<float*>(sptr + OFF_RED);
    float* s_red2 = reinterpret_cast<float*>(sptr + OFF_RED2);
    float* s_loc = reinterpret_cast<float*>(sptr + OFF_LOC);

    if (warp == 9) {
        const int ob = lane >> 3, oc = lane & 7;
        const float xown = __bfloat162float(x[ob * DM + cgrp * 8 + oc]);
        float mean_o = 0.f, sd_o = 1.f;
        if (!odd) {
            uint4 xv[NB][2];
#pragma unroll
            for (int b = 0; b < NB; b++) {
                xv[b][0] = ldg128(x + b * DM + lane * 8);
                xv[b][1] = ldg128(x + b * DM + 256 + lane * 8);
            }
            constexpr int N16 = sizeof(Scratch) / 16 / 64;
            uint4* p = reinterpret_cast<uint4*>(&g_scr) + (size_t)cgrp * N16;
            const uint4 z = make_uint4(0, 0, 0, 0);
#pragma unroll 4
            for (int i = lane; i < N16; i += 32) p[i] = z;
#pragma unroll
            for (int b = 0; b < NB; b++) {
                float v[16], mb, sb_;
                unpack8(xv[b][0], v);
                unpack8(xv[b][1], v + 8);
                ln_stats(v, mb, sb_);
                if (b == ob) { mean_o = mb; sd_o = sb_; }
            }
            __threadfence();
        }
        bar_sync(1, 288);
        float u0 = 0.f, u1 = 0.f;
#pragma unroll
        for (int w = 0; w < 8; w++) {
            u0 += s_red2[w * 96 + oc * 4 + ob];
            u1 += s_red2[w * 96 + 32 + oc * 4 + ob];
        }
        u0 = rbf(u0);
        u1 = rbf(1.0f + rbf(u1));
        if (!odd) {
            const float h = ln_mod(xown, mean_o, sd_o, u1, u0);
            const uint4 r = make_record(h, lane, cgrp);
            stx128(&g_h[((lane >> 2) * 64 + cgrp) * 16 + (lane & 3) * 4], r);
        }
        bar_sync(2, 288);
        {
            float u2 = 0.f;
#pragma unroll
            for (int w = 0; w < 8; w++) u2 += s_red2[w * 96 + 64 + oc * 4 + ob];
            s_loc[lane] = rbf(u2);
            s_loc[32 + lane] = xown;
        }
        const uint4 r0 = make_record(u0, lane, cgrp), r1 = make_record(u1, lane, cgrp);
        bar_sync(6, 288);
        if (odd && lane < 8) stx128(&g_scr.sbcb[((lane >> 2) * 64 + cgrp) * 16 + (lane & 3) * 4], (lane & 4) ? r1 : r0);
        return;
    }

    const int g = lane >> 2, t = lane & 3;
    STAMP(0);
    int krel[2];
#pragma unroll
    for (int e = 0; e < 2; e++)
        krel[e] = warp * 64 + 8 * ((lane & 7) >> 1) + 2 * ((2 * e + (lane >> 4) + ((lane & 7) >> 1)) & 3) + (lane & 1);
    const int mch = (lane >> 3) & 1;
    const int rec_off = (warp * 8 + (g >> 2) * 4 + t) * 16 + (g & 3) * 4;

    {
        uint32_t cw[4];
        const uint32_t* cp = reinterpret_cast<const uint32_t*>(cvec) + (g & 3) * 256 + warp * 32 + ((g >> 2) * 4 + t) * 4;
#pragma unroll
        for (int s = 0; s < 4; s++) cw[s] = __ldg(cp + ((s + t) & 3));
#pragma unroll
        for (int s = 0; s < 4; s++) {
            const float a = bf_lo(cw[s]), b = bf_hi(cw[s]);
            cw[s] = pack_bf16(__fdiv_rn(a, 1.0f + expf(-a)), __fdiv_rn(b, 1.0f + expf(-b)));
        }
        bar_sync(3, 288);
        float d[2][4] = {{0.f, 0.f, 0.f, 0.f}, {0.f, 0.f, 0.f, 0.f}}, r[4];
        mbar_wait(bar_full, 0);
#pragma unroll
        for (int hf = 0; hf < 2; hf++)
#pragma unroll
            for (int e = 0; e < 2; e++) {
                uint32_t a[4];
                ldsm4t(a, sbase + mch * 8192 + (krel[e] + hf * 32) * 16);
                mma16816(d[hf], a, cw[2 * e], cw[2 * e + 1]);
            }
        fold_halves(d[0], d[1], t, r);
        if (t < 2) {
            *reinterpret_cast<float2*>(s_red2 + warp * 96 + g * 4 + 2 * t) = make_float2(r[0], r[1]);
            *reinterpret_cast<float2*>(s_red2 + warp * 96 + 32 + g * 4 + 2 * t) = make_float2(r[2], r[3]);
        }
        bar_arrive(1, 288);
        uint32_t af[2][2][2][4];
        mbar_wait(bar_full + (1 + (warp >> 2)) * 8, 0);
#pragma unroll
        for (int hf = 0; hf < 2; hf++)
#pragma unroll
            for (int e = 0; e < 2; e++) {
                const int k = krel[e] + hf * 32;
#pragma unroll
                for (int mt = 0; mt < 2; mt++)
                    ldsm4t(af[hf][e][mt], sbase + SLOT + k * 64 + (((mt * 2 + mch) ^ ((k >> 1) & 3)) << 4));
            }
        {
            float d2[2][4] = {{0.f, 0.f, 0.f, 0.f}, {0.f, 0.f, 0.f, 0.f}};
            mbar_wait(bar_full + 3 * 8, 0);
#pragma unroll
            for (int hf = 0; hf < 2; hf++)
#pragma unroll
                for (int e = 0; e < 2; e++) {
                    uint32_t a[4];
                    ldsm4t(a, sbase + 3 * SLOT + (krel[e] + hf * 32) * 16);
                    mma16816(d2[hf], a, cw[2 * e], cw[2 * e + 1]);
                }
            fold_halves(d2[0], d2[1], t, r);
            if (t < 2) *reinterpret_cast<float2*>(s_red2 + warp * 96 + 64 + g * 4 + 2 * t) = make_float2(r[0], r[1]);
            bar_arrive(2, 288);
        }
        STAMP(1);
        uint4 hv;
        {
            const uint32_t* hp = g_h + (cta & (NREP - 1)) * 1024 + rec_off;
            unsigned it = 0;
            hv = ldx128(hp);
            while (!ok4(hv) && ++it < SPIN_LIMIT) { __nanosleep(64); hv = ldx128(hp); }
        }
        __syncwarp();
        float dq[2][2][4];
#pragma unroll
        for (int hf = 0; hf < 2; hf++)
#pragma unroll
            for (int mt = 0; mt < 2; mt++) {
                dq[hf][mt][0] = dq[hf][mt][1] = dq[hf][mt][2] = dq[hf][mt][3] = 0.f;
                mma16816(dq[hf][mt], af[hf][0][mt], hv.x, hv.y);
                mma16816(dq[hf][mt], af[hf][1][mt], hv.z, hv.w);
            }
#pragma unroll
        for (int mt = 0; mt < 2; mt++) {
            fold_halves(dq[0][mt], dq[1][mt], t, r);
            if (t < 2) {
                float* p = s_red + warp * 128 + 2 * t * 32 + mt * 16 + g;
                p[0] = r[0]; p[32] = r[1]; p[8] = r[2]; p[40] = r[3];
            }
        }
        __threadfence();
        bar_sync(6, 288);
        if (warp < 4 && lane < 4) mbar_arrive(bar_empty + lane * 8);
        if (tid < 64) {
            const int b = tid >> 4, cp2 = tid & 15;
            float s0 = 0.f, s1 = 0.f;
#pragma unroll
            for (int w = 0; w < 8; w++) {
                float2 v = *reinterpret_cast<const float2*>(s_red + w * 128 + b * 32 + 2 * cp2);
                s0 += v.x; s1 += v.y;
            }
            stx32(&g_scr.q[b * (HQ * 64) + cta * 16 + cp2], nz(pack_bf16(s0, s1)));
        }
    }
    STAMP(2);

    const int pair = cta >> 2, split = cta & 3;
    const int ab = pair >> 3, kvh = pair & 7;
    uint32_t qf[4][4];
    {
        if (tid >= 64 && tid < 128) {
            const int i = tid - 64;
            const uint32_t* qp = g_scr.q + (ab * HQ + kvh * 4) * 64 + i * 4;
            unsigned it = 0;
            uint4 v = ldx128(qp);
            while (!ok4(v) && ++it < SPIN_LIMIT) { __nanosleep(64); v = ldx128(qp); }
            *reinterpret_cast<uint4*>(sptr + OFF_SO + (i >> 4) * 272 + (i & 15) * 16) = v;
        }
        bar_sync(5, 256);
#pragma unroll
        for (int kp = 0; kp < 4; kp++) ldsm4(qf[kp], sbase + OFF_SO + (lane & 3) * 272 + kp * 64 + (lane >> 3) * 16);
    }
    STAMP(3);

    float o[8][4];
#pragma unroll
    for (int i = 0; i < 8; i++) { o[i][0] = o[i][1] = o[i][2] = o[i][3] = 0.f; }
    float m0 = -INFINITY, m1 = -INFINITY, l0 = 0.f, l1 = 0.f;
    {
        const int grp = warp >> 2, r0 = (warp & 3) * 16;
        const int krow = r0 + (lane & 7) + ((lane >> 3) & 1) * 8;
        const int vrow = r0 + (lane & 7) + (lane >> 4) * 8;
        const uint32_t koff = krow * 128, kx = krow & 7, kc = lane >> 4;
        const uint32_t voff = vrow * 128, vx = vrow & 7, vc = (lane >> 3) & 1;
        int slot = IT_KV + 2 * grp, ph = 0;
        const float scale = 0.08838834764831845f;
        for (int j = grp; j < NTILE; j += 2) {
            const uint32_t kb = sbase + slot * SLOT, vb = kb + SLOT;
            mbar_wait(bar_full + slot * 8, ph);
            float s[2][4] = {{0.f, 0.f, 0.f, 0.f}, {0.f, 0.f, 0.f, 0.f}};
#pragma unroll
            for (int ks = 0; ks < 8; ks++) {
                uint32_t a[4];
                ldsm4(a, kb + (ks >> 2) * 8192 + koff + ((((ks & 3) * 2 + kc) ^ kx) << 4));
                mma16816(s[ks & 1], a, qf[ks >> 1][(ks & 1) * 2], qf[ks >> 1][(ks & 1) * 2 + 1]);
            }
            __syncwarp();
            if (lane == 0) mbar_arrive(bar_empty + slot * 8);
            float sv[4];
#pragma unroll
            for (int i = 0; i < 4; i++) sv[i] = rbf(rbf(s[0][i] + s[1][i]) * scale);
            float t0 = fmaxf(sv[0], sv[2]), t1 = fmaxf(sv[1], sv[3]);
#pragma unroll
            for (int off = 4; off < 32; off <<= 1) {
                t0 = fmaxf(t0, __shfl_xor_sync(0xffffffffu, t0, off));
                t1 = fmaxf(t1, __shfl_xor_sync(0xffffffffu, t1, off));
            }
            const float n0 = fmaxf(m0, t0), n1 = fmaxf(m1, t1);
            if (__any_sync(0xffffffffu, (n0 != m0) || (n1 != m1))) {
                const float a0 = ex2((m0 - n0) * LOG2E), a1 = ex2((m1 - n1) * LOG2E);
                l0 *= a0; l1 *= a1;
#pragma unroll
                for (int i = 0; i < 8; i++) { o[i][0] *= a0; o[i][1] *= a1; o[i][2] *= a0; o[i][3] *= a1; }
                m0 = n0; m1 = n1;
            }
            const float p0 = ex2((sv[0] - m0) * LOG2E), p1 = ex2((sv[1] - m1) * LOG2E);
            const float p2 = ex2((sv[2] - m0) * LOG2E), p3 = ex2((sv[3] - m1) * LOG2E);
            l0 += p0 + p2; l1 += p1 + p3;
            const uint32_t b0 = movmat(pack_bf16(p0, p1)), b1 = movmat(pack_bf16(p2, p3));
            mbar_wait(bar_full + slot * 8 + 8, ph);
#pragma unroll
            for (int mt = 0; mt < 8; mt++) {
                uint32_t a[4];
                ldsm4t(a, vb + (mt >> 2) * 8192 + voff + ((((mt & 3) * 2 + vc) ^ vx) << 4));
                mma16816(o[mt], a, b0, b1);
            }
            __syncwarp();
            if (lane == 0) mbar_arrive(bar_empty + slot * 8 + 8);
            slot += 4;
            if (slot >= NSLOT) { slot -= NSLOT; ph ^= 1; }
        }
    }
    STAMP(4);
    {
        float* s_mrg = reinterpret_cast<float*>(sptr + OFF_MRG);
        float* s_ml = reinterpret_cast<float*>(sptr + OFF_ML);
#pragma unroll
        for (int off = 4; off < 32; off <<= 1) {
            l0 += __shfl_xor_sync(0xffffffffu, l0, off);
            l1 += __shfl_xor_sync(0xffffffffu, l1, off);
        }
        if (t < 2) {
            float* p0 = s_mrg + (warp * 4 + 2 * t) * 132 + g;
#pragma unroll
            for (int mt = 0; mt < 8; mt++) {
                p0[mt * 16] = o[mt][0];
                p0[132 + mt * 16] = o[mt][1];
                p0[mt * 16 + 8] = o[mt][2];
                p0[132 + mt * 16 + 8] = o[mt][3];
            }
            if (g == 0) *reinterpret_cast<float4*>(s_ml + (warp * 4 + 2 * t) * 2) = make_float4(m0, l0, m1, l1);
        }
        bar_sync(5, 256);
        const int hd = tid >> 6, dp = tid & 63;
        float mw[8], lw[8], M = -INFINITY;
#pragma unroll
        for (int w = 0; w < 8; w++) {
            float2 v = *reinterpret_cast<const float2*>(s_ml + (w * 4 + hd) * 2);
            mw[w] = v.x; lw[w] = v.y;
            M = fmaxf(M, v.x);
        }
        float a0 = 0.f, a1 = 0.f, L = 0.f;
#pragma unroll
        for (int w = 0; w < 8; w++) {
            const float f = ex2((mw[w] - M) * LOG2E);
            float2 v = *reinterpret_cast<const float2*>(s_mrg + (w * 4 + hd) * 132 + 2 * dp);
            a0 = fmaf(f, v.x, a0); a1 = fmaf(f, v.y, a1); L = fmaf(f, lw[w], L);
        }
        const int rec = ((kvh * 4 + hd) * NB + ab) * 4 + split;
        stx64(&g_scr.po[rec * DH + 2 * dp], nzf(a0), nzf(a1));
        if (dp == 0) stx64(&g_scr.pml[rec * 2], nzf(M), nzf(L));
    }
    STAMP(5);
    uint4 sbv, cbv;
    {
        const int hh = cta >> 2;
        const int b = tid >> 6, d8 = (tid >> 2) & 15, sp = tid & 3;
        const int rec = (hh * NB + b) * 4 + sp;
        const uint32_t* op = g_scr.po + rec * DH + d8 * 8;
        const uint32_t* mp = g_scr.pml + rec * 2;
        uint4 v0, v1;
        uint2 ml;
        unsigned it = 0;
        do {
            sbv = ldx128(g_scr.sbcb + rec_off);
            cbv = ldx128(g_scr.sbcb + 1024 + rec_off);
        } while (!(ok4(sbv) && ok4(cbv)) && ++it < SPIN_LIMIT);
        bool ok;
        do {
            v0 = ldx128(op);
            v1 = ldx128(op + 4);
            ml = ldx64(mp);
            ok = ok4(v0) && ok4(v1) && ok2(ml);
        } while (!ok && ++it < SPIN_LIMIT);
        __syncwarp();
        const float ms = __uint_as_float(ml.x);
        float M = fmaxf(ms, __shfl_xor_sync(0xffffffffu, ms, 1));
        M = fmaxf(M, __shfl_xor_sync(0xffffffffu, M, 2));
        const float f = ex2((ms - M) * LOG2E);
        float L = f * __uint_as_float(ml.y);
        L += __shfl_xor_sync(0xffffffffu, L, 1);
        L += __shfl_xor_sync(0xffffffffu, L, 2);
        const float fw = __fdiv_rn(f, L);
        float a[8] = {fw * __uint_as_float(v0.x), fw * __uint_as_float(v0.y), fw * __uint_as_float(v0.z), fw * __uint_as_float(v0.w),
                      fw * __uint_as_float(v1.x), fw * __uint_as_float(v1.y), fw * __uint_as_float(v1.z), fw * __uint_as_float(v1.w)};
        bfly<8>(a, lane, 2);
        bfly<4>(a, lane, 1);
        *reinterpret_cast<uint32_t*>(sptr + OFF_SO + b * 272 + (d8 * 8 + sp * 2) * 2) = pack_bf16(a[0], a[1]);
        STAMP(6);
        static_assert(slot_of(IT_WO) + 1 == slot_of(IT_WO + 1) && phase_of(IT_WO) == phase_of(IT_WO + 1), "wo items");
        const int half = warp >> 2;
        mbar_wait(bar_full + (slot_of(IT_WO) + half) * 8, phase_of(IT_WO));
        uint32_t af[8][4];
        {
            const uint32_t wb = sbase + (slot_of(IT_WO) + half) * SLOT;
            const int krow = (lane & 7) + (lane >> 4) * 8;
            const uint32_t ch = (warp & 3) * 2 + mch;
#pragma unroll
            for (int ks = 0; ks < 8; ks++) ldsm4t(af[ks], wb + (ks * 16 + krow) * 128 + ((ch ^ (krow & 7)) << 4));
        }
        bar_sync(5, 256);
        float d[2][4] = {{0.f, 0.f, 0.f, 0.f}, {0.f, 0.f, 0.f, 0.f}};
#pragma unroll
        for (int kp = 0; kp < 4; kp++) {
            uint32_t bf[4];
            ldsm4(bf, sbase + OFF_SO + (lane & 3) * 272 + kp * 64 + (lane >> 3) * 16);
            mma16816(d[0], af[2 * kp], bf[0], bf[1]);
            mma16816(d[1], af[2 * kp + 1], bf[2], bf[3]);
        }
        if (t < 2) {
            uint32_t* p = g_scr.wop + (((cta & 3) * 16 + warp * 2) * HQ + hh) * 32 + g * 4 + 2 * t;
            stx64(p, nzf(d[0][0] + d[1][0]), nzf(d[0][1] + d[1][1]));
            stx64(p + HQ * 32, nzf(d[0][2] + d[1][2]), nzf(d[0][3] + d[1][3]));
        }
    }
    STAMP(7);
    if (!odd && warp == 0) {
        const uint32_t* p = g_scr.wop + cgrp * (HQ * 32) + lane * 4;
        uint4 v[8];
        unsigned it = 0;
        bool ok;
        do {
            ok = true;
#pragma unroll
            for (int i = 0; i < 8; i++) v[i] = ldx128(p + i * 128);
#pragma unroll
            for (int i = 0; i < 8; i++) ok = ok && ok4(v[i]);
        } while (!ok && ++it < SPIN_LIMIT);
        __syncwarp();
        float a[4] = {0.f, 0.f, 0.f, 0.f};
#pragma unroll
        for (int i = 0; i < 8; i++) {
            a[0] += __uint_as_float(v[i].x); a[1] += __uint_as_float(v[i].y);
            a[2] += __uint_as_float(v[i].z); a[3] += __uint_as_float(v[i].w);
        }
        bfly<4>(a, lane, 16);
        bfly<2>(a, lane, 8);
        const float x1 = rbf(s_loc[32 + lane] + rbf(s_loc[lane] * rbf(a[0])));
        const uint4 r = make_record(x1, lane, cgrp);
        stx128(&g_scr.x1[((lane >> 2) * 64 + cgrp) * 16 + (lane & 3) * 4], r);
    }
    STAMP(8);
    if (cta < NFFN) {
        constexpr int SG = slot_of(IT_WO + 2), SU = slot_of(IT_WO + 3), SD = slot_of(IT_WO + 4);
        uint32_t ag[2][2][4], au[2][2][4];
        mbar_wait(bar_full + SG * 8, phase_of(IT_WO + 2));
        mbar_wait(bar_full + SU * 8, phase_of(IT_WO + 3));
#pragma unroll
        for (int hf = 0; hf < 2; hf++)
#pragma unroll
            for (int e = 0; e < 2; e++) {
                const int k = krel[e] + hf * 32;
                const uint32_t off = k * 32 + ((mch ^ ((k >> 2) & 1)) << 4);
                ldsm4t(ag[hf][e], sbase + SG * SLOT + off);
                ldsm4t(au[hf][e], sbase + SU * SLOT + off);
            }
        uint32_t hw[4];
        {
            const uint32_t* p = g_scr.x1 + (cta & (NREP - 1)) * 1024 + rec_off;
            uint4 xv;
            unsigned it = 0;
            do { xv = ldx128(p); } while (!ok4(xv) && ++it < SPIN_LIMIT);
            __syncwarp();
            float v[8];
            unpack8(xv, v);
            float s = ((v[0] + v[1]) + (v[2] + v[3])) + ((v[4] + v[5]) + (v[6] + v[7]));
            s += __shfl_xor_sync(0xffffffffu, s, 1);
            s += __shfl_xor_sync(0xffffffffu, s, 2);
            s += __shfl_xor_sync(0xffffffffu, s, 16);
            const float mw = s * (1.0f / 64.0f);
            float q = 0.f;
#pragma unroll
            for (int i = 0; i < 8; i++) { const float dd = v[i] - mw; q = fmaf(dd, dd, q); }
            q += __shfl_xor_sync(0xffffffffu, q, 1);
            q += __shfl_xor_sync(0xffffffffu, q, 2);
            q += __shfl_xor_sync(0xffffffffu, q, 16);
            float2* st = reinterpret_cast<float2*>(sptr + OFF_ST);
            if (t == 0 && g < 4) st[warp * 4 + g] = make_float2(mw, q);
            bar_sync(5, 256);
            float2 pw[8];
            float mean = 0.f, m2 = 0.f;
#pragma unroll
            for (int w = 0; w < 8; w++) { pw[w] = st[w * 4 + (g & 3)]; mean += pw[w].x; m2 += pw[w].y; }
            mean *= 0.125f;
            float dv = 0.f;
#pragma unroll
            for (int w = 0; w < 8; w++) { const float dd = pw[w].x - mean; dv = fmaf(dd, dd, dv); }
            const float var = fmaf(dv, 64.0f, m2) * (1.0f / DM);
            const float mb = rbf(mean), sd = rbf(sqrtf(rbf(rbf(var) + 1e-5f)));
            float sbf[8], cbf[8], r[8];
            unpack8(sbv, sbf);
            unpack8(cbv, cbf);
#pragma unroll
            for (int i = 0; i < 8; i++) r[i] = ln_mod(v[i], mb, sd, cbf[i], sbf[i]);
#pragma unroll
            for (int i = 0; i < 4; i++) hw[i] = pack_bf16(r[2 * i], r[2 * i + 1]);
        }
        STAMP(9);
        {
            float dg[2][4], du[2][4], rg[4], ru[4];
#pragma unroll
            for (int hf = 0; hf < 2; hf++) {
                dg[hf][0] = dg[hf][1] = dg[hf][2] = dg[hf][3] = 0.f;
                du[hf][0] = du[hf][1] = du[hf][2] = du[hf][3] = 0.f;
                mma16816(dg[hf], ag[hf][0], hw[0], hw[1]);
                mma16816(du[hf], au[hf][0], hw[0], hw[1]);
                mma16816(dg[hf], ag[hf][1], hw[2], hw[3]);
                mma16816(du[hf], au[hf][1], hw[2], hw[3]);
            }
            fold_halves(dg[0], dg[1], t, rg);
            fold_halves(du[0], du[1], t, ru);
            if (t < 2) {
                float* p = s_red + warp * 128 + g * 8 + t * 4;
                *reinterpret_cast<float4*>(p) = make_float4(rg[0], ru[0], rg[1], ru[1]);
                *reinterpret_cast<float4*>(p + 64) = make_float4(rg[2], ru[2], rg[3], ru[3]);
            }
        }
        if (cta < 64 && warp == 7) *reinterpret_cast<uint4*>(g_h + cta * 128 + lane * 4) = make_uint4(0, 0, 0, 0);
        uint32_t ad[4][4];
        {
            mbar_wait(bar_full + SD * 8, phase_of(IT_WO + 4));
            const int krow = (lane & 7) + (lane >> 4) * 8;
#pragma unroll
            for (int mt = 0; mt < 4; mt++) {
                const uint32_t ch = mt * 2 + mch;
                ldsm4t(ad[mt], sbase + SD * SLOT + warp * 2048 + krow * 128 + ((ch ^ (krow & 7)) << 4));
            }
        }
        bar_sync(5, 256);
        if (tid < 64) {
            float gsum = 0.f, usum = 0.f;
#pragma unroll
            for (int w = 0; w < 8; w++) {
                float2 v = *reinterpret_cast<const float2*>(s_red + w * 128 + tid * 2);
                gsum += v.x; usum += v.y;
            }
            const float gv = rbf(gsum), uv = rbf(usum);
            const float inner = 0.7978845608028654f * (gv + 0.044715f * gv * gv * gv);
            const float ge = rbf(0.5f * gv * (1.0f + tanhf(inner)));
            const int col = tid >> 2, b = tid & 3;
            *reinterpret_cast<bf16*>(sptr + OFF_ACT + b * 48 + col * 2) = __float2bfloat16_rn(ge * uv);
        }
        bar_sync(5, 256);
        {
            uint32_t bf[2];
            ldsm2(bf, sbase + OFF_ACT + (lane & 3) * 48 + mch * 16);
            uint32_t* p = g_scr.dnp + (warp * 8 * NFFN + cta) * 32 + g * 4 + 2 * t;
#pragma unroll
            for (int mt = 0; mt < 4; mt++) {
                float d[4] = {0.f, 0.f, 0.f, 0.f};
                mma16816(d, ad[mt], bf[0], bf[1]);
                if (t < 2) {
                    stx64(p + (2 * mt) * (NFFN * 32), nzf(d[0]), nzf(d[1]));
                    stx64(p + (2 * mt + 1) * (NFFN * 32), nzf(d[2]), nzf(d[3]));
                }
            }
        }
    }
    STAMP(10);
    if (odd) {
        const uint32_t* p = g_scr.dnp + cgrp * (NFFN * 32) + tid * 4;
        uint32_t x1w = 1;
        unsigned it = 0;
        if (warp == 0) {
            const uint32_t* xp = g_scr.x1 + cgrp * 16 + (lane >> 3) * 4 + ((((lane & 7) >> 1) - cgrp) & 3);
            do { x1w = ldx32(xp); } while (!x1w && ++it < SPIN_LIMIT);
        }
        uint4 v[4];
        v[3] = make_uint4(0x80000000u, 0x80000000u, 0x80000000u, 0x80000000u);
        bool ok;
        do {
            v[0] = ldx128(p);
            v[1] = ldx128(p + 1024);
            v[2] = ldx128(p + 2048);
            if (tid < 128) v[3] = ldx128(p + 3072);
            ok = ok4(v[0]) && ok4(v[1]) && ok4(v[2]) && ok4(v[3]);
        } while (!ok && ++it < SPIN_LIMIT);
        __syncwarp();
        float a[4];
        a[0] = (__uint_as_float(v[0].x) + __uint_as_float(v[1].x)) + (__uint_as_float(v[2].x) + __uint_as_float(v[3].x));
        a[1] = (__uint_as_float(v[0].y) + __uint_as_float(v[1].y)) + (__uint_as_float(v[2].y) + __uint_as_float(v[3].y));
        a[2] = (__uint_as_float(v[0].z) + __uint_as_float(v[1].z)) + (__uint_as_float(v[2].z) + __uint_as_float(v[3].z));
        a[3] = (__uint_as_float(v[0].w) + __uint_as_float(v[1].w)) + (__uint_as_float(v[2].w) + __uint_as_float(v[3].w));
        bfly<4>(a, lane, 16);
        bfly<2>(a, lane, 8);
        s_red2[warp * 32 + lane] = a[0];
        bar_sync(5, 256);
        if (warp == 0) {
            float f = 0.f;
#pragma unroll
            for (int w = 0; w < 8; w++) f += s_red2[w * 32 + lane];
            const float x1 = (lane & 1) ? bf_hi(x1w) : bf_lo(x1w);
            const float r = x1 + rbf(s_loc[lane] * rbf(f));
            out[(lane >> 3) * DM + cgrp * 8 + (lane & 7)] = __float2bfloat16_rn(r);
        }
    }
    STAMP(11);
}

typedef CUresult (*EncodeFn)(CUtensorMap*, CUtensorMapDataType, cuuint32_t, void*, const cuuint64_t*, const cuuint64_t*,
                             const cuuint32_t*, const cuuint32_t*, CUtensorMapInterleave, CUtensorMapSwizzle,
                             CUtensorMapL2promotion, CUtensorMapFloatOOBfill);

void encode(EncodeFn fn, CUtensorMap* m, const void* base, int rank, const cuuint64_t* dims, const cuuint64_t* strides,
            const cuuint32_t* box, CUtensorMapSwizzle sw, CUtensorMapL2promotion promo) {
    cuuint32_t es[3] = {1, 1, 1};
    fn(m, CU_TENSOR_MAP_DATA_TYPE_BFLOAT16, rank, const_cast<void*>(base), dims, strides, box, es,
       CU_TENSOR_MAP_INTERLEAVE_NONE, sw, promo, CU_TENSOR_MAP_FLOAT_OOB_FILL_NONE);
}

}

extern "C" void kernel_launch(void* const* d_in, const int* in_sizes, int n_in, void* d_out, int out_size) {
    (void)in_sizes; (void)n_in; (void)out_size;
    const bf16* x = (const bf16*)d_in[0];
    const bf16* kc = (const bf16*)d_in[1];
    const bf16* vc = (const bf16*)d_in[2];
    const bf16* wq = (const bf16*)d_in[3];
    const bf16* wo = (const bf16*)d_in[4];
    const bf16* wg = (const bf16*)d_in[6];
    const bf16* wu = (const bf16*)d_in[7];
    const bf16* wd = (const bf16*)d_in[8];
    const bf16* cv = (const bf16*)d_in[9];
    const bf16* wm = (const bf16*)d_in[10];

    static EncodeFn fn = nullptr;
    if (!fn) {
        void* p = nullptr;
        cudaDriverEntryPointQueryResult st;
        cudaGetDriverEntryPoint("cuTensorMapEncodeTiled", &p, cudaEnableDefault, &st);
        fn = (EncodeFn)p;
        cudaFuncSetAttribute(fused_kernel, cudaFuncAttributeMaxDynamicSharedMemorySize, SMEM_BYTES);
    }
    CUtensorMap tmK, tmV, tmM, tmQ, tmWo, tmG, tmU, tmD;
    {
        cuuint64_t dims[2] = {6 * DM, DM};
        cuuint64_t strides[1] = {6 * DM * 2};
        cuuint32_t box[2] = {8, 256};
        encode(fn, &tmM, wm, 2, dims, strides, box, CU_TENSOR_MAP_SWIZZLE_NONE, CU_TENSOR_MAP_L2_PROMOTION_L2_128B);
    }
    {
        cuuint64_t dims[2] = {HQ * DH, DM};
        cuuint64_t strides[1] = {HQ * DH * 2};
        cuuint32_t box[2] = {32, 256};
        encode(fn, &tmQ, wq, 2, dims, strides, box, CU_TENSOR_MAP_SWIZZLE_64B, CU_TENSOR_MAP_L2_PROMOTION_L2_128B);
    }
    {
        cuuint64_t dims[3] = {64, (cuuint64_t)NB * HKV * SK, 2};
        cuuint64_t strides[2] = {256, 128};
        cuuint32_t box[3] = {64, TK, 2};
        encode(fn, &tmK, kc, 3, dims, strides, box, CU_TENSOR_MAP_SWIZZLE_128B, CU_TENSOR_MAP_L2_PROMOTION_L2_256B);
        encode(fn, &tmV, vc, 3, dims, strides, box, CU_TENSOR_MAP_SWIZZLE_128B, CU_TENSOR_MAP_L2_PROMOTION_L2_256B);
    }
    {
        cuuint64_t dims[2] = {DM, HQ * DH};
        cuuint64_t strides[1] = {DM * 2};
        cuuint32_t box[2] = {64, 128};
        encode(fn, &tmWo, wo, 2, dims, strides, box, CU_TENSOR_MAP_SWIZZLE_128B, CU_TENSOR_MAP_L2_PROMOTION_L2_256B);
    }
    {
        cuuint64_t dims[2] = {FF, DM};
        cuuint64_t strides[1] = {FF * 2};
        cuuint32_t box[2] = {16, 256};
        encode(fn, &tmG, wg, 2, dims, strides, box, CU_TENSOR_MAP_SWIZZLE_32B, CU_TENSOR_MAP_L2_PROMOTION_L2_128B);
        encode(fn, &tmU, wu, 2, dims, strides, box, CU_TENSOR_MAP_SWIZZLE_32B, CU_TENSOR_MAP_L2_PROMOTION_L2_128B);
    }
    {
        cuuint64_t dims[3] = {64, FF, 8};
        cuuint64_t strides[2] = {DM * 2, 128};
        cuuint32_t box[3] = {64, 16, 8};
        encode(fn, &tmD, wd, 3, dims, strides, box, CU_TENSOR_MAP_SWIZZLE_128B, CU_TENSOR_MAP_L2_PROMOTION_L2_256B);
    }
    fused_kernel<<<NCTA, NTHREADS, SMEM_BYTES>>>(tmK, tmV, tmM, tmQ, tmWo, tmG, tmU, tmD, x, cv, (bf16*)d_out);
}
```

```cpp
#include <cuda_runtime.h>
#include <cuda_bf16.h>
#include <cuda.h>
#include <stdint.h>

typedef __nv_bfloat16 bf16;

namespace {

constexpr int NB = 4, DM = 512, HQ = 32, HKV = 8, SK = 8192, DH = 128, FF = 1792;
constexpr int NCTA = 128;
constexpr int NSLOT = 12;
constexpr int SLOT = 16384;
constexpr int TK = 64;
constexpr int NTILE = 32;
constexpr int IT_KV = 4;
constexpr int IT_WO = IT_KV + 2 * NTILE;
#define INFLIGHT 4
constexpr int NFFN = FF / 16;
constexpr int NREP = 8;
constexpr int NTHREADS = 320;
constexpr unsigned SPIN_LIMIT = 1u << 22;
constexpr float LOG2E = 1.4426950408889634f;

struct __align__(128) TailScratch {
    uint32_t po[HQ * NB * 4 * DH];
    uint32_t pml[HQ * NB * 4 * 2];
    uint32_t wop[64 * HQ * 32];
    uint32_t x1[NREP * 64 * 16];
    uint32_t dnp[64 * NFFN * 32];
};
static_assert(sizeof(TailScratch) % (NCTA * 16) == 0, "scratch must split evenly");
struct __align__(128) HeadScratch {
    uint32_t h[NREP * 64 * 16];
    uint32_t q[NB * HQ * 64];
    uint32_t sbcb[2 * 64 * 16];
};
static_assert(sizeof(HeadScratch) == 72 * 1024, "head scratch is cleared by 72 CTAs x 1 KB");
__device__ TailScratch g_t;
__device__ HeadScratch g_hd;
__device__ unsigned g_cnt;
#define STAMP(i) do {} while (0)
#define STAMPW(i) do {} while (0)

constexpr int MRG_G = 20, MRG_H = 8 * MRG_G + 4;
constexpr int OFF_MRG = NSLOT * SLOT;
constexpr int OFF_ML = OFF_MRG + 32 * MRG_H * 4;
constexpr int OFF_RED = OFF_ML + 8 * 4 * 2 * 4;
constexpr int OFF_RED2 = OFF_RED + 8 * 128 * 4;
constexpr int OFF_SO = OFF_RED2 + 8 * 96 * 4;
constexpr int OFF_ST = OFF_SO + 4 * 136 * 2;
constexpr int OFF_ACT = OFF_ST + 8 * 4 * 8;
constexpr int OFF_LOC = OFF_ACT + 4 * 24 * 2;
constexpr int OFF_BAR = OFF_LOC + 64 * 4;
constexpr int SMEM_USED = OFF_BAR + 2 * NSLOT * 8;
constexpr int SMEM_BYTES = SMEM_USED + 1024;
static_assert(SMEM_BYTES <= 232448, "too much smem");
static_assert(OFF_BAR % 8 == 0 && OFF_SO % 16 == 0 && OFF_ST % 16 == 0 && OFF_ACT % 16 == 0 && OFF_ML % 16 == 0, "align");
__host__ __device__ constexpr int slot_of(int item) { return item % NSLOT; }
__host__ __device__ constexpr int phase_of(int item) { return (item / NSLOT) & 1; }

__device__ __forceinline__ uint32_t smem_u32(const void* p) { return (uint32_t)__cvta_generic_to_shared(p); }
__device__ __forceinline__ void mbar_init(uint32_t bar, int cnt) { asm volatile("mbarrier.init.shared::cta.b64 [%0], %1;" ::"r"(bar), "r"(cnt) : "memory"); }
__device__ __forceinline__ void mbar_expect_tx(uint32_t bar, uint32_t bytes) { asm volatile("mbarrier.arrive.expect_tx.shared::cta.b64 _, [%0], %1;" ::"r"(bar), "r"(bytes) : "memory"); }
__device__ __forceinline__ void mbar_arrive(uint32_t bar) { asm volatile("mbarrier.arrive.shared::cta.b64 _, [%0];" ::"r"(bar) : "memory"); }
__device__ __forceinline__ bool mbar_try(uint32_t bar, uint32_t parity) {
    uint32_t ok;
    asm volatile("{\n.reg .pred p;\nmbarrier.try_wait.parity.shared::cta.b64 p, [%1], %2;\nselp.u32 %0, 1, 0, p;\n}" : "=r"(ok) : "r"(bar), "r"(parity) : "memory");
    return ok != 0;
}
__device__ __forceinline__ void mbar_wait(uint32_t bar, uint32_t parity) {
    unsigned it = 0;
#pragma unroll 1
    while (!mbar_try(bar, parity)) { if (++it > SPIN_LIMIT) break; }
}
__device__ __forceinline__ void tma2d(uint32_t dst, const CUtensorMap* m, int c0, int c1, uint32_t bar) {
    asm volatile("cp.async.bulk.tensor.2d.shared::cluster.global.mbarrier::complete_tx::bytes [%0], [%1, {%3, %4}], [%2];" ::"r"(dst), "l"(m), "r"(bar), "r"(c0), "r"(c1) : "memory");
}
__device__ __forceinline__ void tma3d(uint32_t dst, const CUtensorMap* m, int c0, int c1, int c2, uint32_t bar) {
    asm volatile("cp.async.bulk.tensor.3d.shared::cluster.global.mbarrier::complete_tx::bytes [%0], [%1, {%3, %4, %5}], [%2];" ::"r"(dst), "l"(m), "r"(bar), "r"(c0), "r"(c1), "r"(c2) : "memory");
}
__device__ __forceinline__ void tma3d_hint(uint32_t dst, const CUtensorMap* m, int c0, int c1, int c2, uint32_t bar, uint64_t pol) {
    asm volatile("cp.async.bulk.tensor.3d.shared::cluster.global.mbarrier::complete_tx::bytes.L2::cache_hint [%0], [%1, {%3, %4, %5}], [%2], %6;" ::"r"(dst), "l"(m), "r"(bar), "r"(c0), "r"(c1), "r"(c2), "l"(pol) : "memory");
}
__device__ __forceinline__ void bar_sync(int id, int n) { asm volatile("bar.sync %0, %1;" ::"r"(id), "r"(n) : "memory"); }
__device__ __forceinline__ void bar_arrive(int id, int n) { asm volatile("bar.arrive %0, %1;" ::"r"(id), "r"(n) : "memory"); }
__device__ __forceinline__ void ldsm4(uint32_t* r, uint32_t addr) {
    asm volatile("ldmatrix.sync.aligned.m8n8.x4.shared.b16 {%0,%1,%2,%3}, [%4];" : "=r"(r[0]), "=r"(r[1]), "=r"(r[2]), "=r"(r[3]) : "r"(addr) : "memory");
}
__device__ __forceinline__ void ldsm4t(uint32_t* r, uint32_t addr) {
    asm volatile("ldmatrix.sync.aligned.m8n8.x4.trans.shared.b16 {%0,%1,%2,%3}, [%4];" : "=r"(r[0]), "=r"(r[1]), "=r"(r[2]), "=r"(r[3]) : "r"(addr) : "memory");
}
__device__ __forceinline__ void ldsm2(uint32_t* r, uint32_t addr) {
    asm volatile("ldmatrix.sync.aligned.m8n8.x2.shared.b16 {%0,%1}, [%2];" : "=r"(r[0]), "=r"(r[1]) : "r"(addr) : "memory");
}
__device__ __forceinline__ void mma16816(float* d, const uint32_t* a, uint32_t b0, uint32_t b1) {
    asm volatile("mma.sync.aligned.m16n8k16.row.col.f32.bf16.bf16.f32 {%0,%1,%2,%3}, {%4,%5,%6,%7}, {%8,%9}, {%0,%1,%2,%3};"
                 : "+f"(d[0]), "+f"(d[1]), "+f"(d[2]), "+f"(d[3]) : "r"(a[0]), "r"(a[1]), "r"(a[2]), "r"(a[3]), "r"(b0), "r"(b1));
}
__device__ __forceinline__ void mma16816z(float* d, const uint32_t* a, uint32_t b0, uint32_t b1) {
    asm volatile("mma.sync.aligned.m16n8k16.row.col.f32.bf16.bf16.f32 {%0,%1,%2,%3}, {%4,%5,%6,%7}, {%8,%9}, {%10,%10,%10,%10};"
                 : "=f"(d[0]), "=f"(d[1]), "=f"(d[2]), "=f"(d[3]) : "r"(a[0]), "r"(a[1]), "r"(a[2]), "r"(a[3]), "r"(b0), "r"(b1), "f"(0.f));
}
__device__ __forceinline__ uint32_t movmat(uint32_t a) {
    uint32_t d;
    asm volatile("movmatrix.sync.aligned.m8n8.trans.b16 %0, %1;" : "=r"(d) : "r"(a));
    return d;
}
__device__ __forceinline__ uint32_t pack_bf16(float lo, float hi) {
    uint32_t r;
    asm("cvt.rn.bf16x2.f32 %0, %1, %2;" : "=r"(r) : "f"(hi), "f"(lo));
    return r;
}
__device__ __forceinline__ float bf_lo(uint32_t w) { return __uint_as_float(w << 16); }
__device__ __forceinline__ float bf_hi(uint32_t w) { return __uint_as_float(w & 0xffff0000u); }
__device__ __forceinline__ float rbf(float x) { return __uint_as_float(pack_bf16(0.f, x)); }
__device__ __forceinline__ float ex2(float x) { float y; asm("ex2.approx.ftz.f32 %0, %1;" : "=f"(y) : "f"(x)); return y; }
__device__ __forceinline__ float rcp(float x) { float y; asm("rcp.approx.f32 %0, %1;" : "=f"(y) : "f"(x)); return y; }
__device__ __forceinline__ float sqrt_a(float x) { float y; asm("sqrt.approx.f32 %0, %1;" : "=f"(y) : "f"(x)); return y; }
__device__ __forceinline__ uint32_t bf2_sub(uint32_t a, uint32_t b) { uint32_t d; asm("sub.rn.bf16x2 %0, %1, %2;" : "=r"(d) : "r"(a), "r"(b)); return d; }
__device__ __forceinline__ uint32_t bf2_add(uint32_t a, uint32_t b) { uint32_t d; asm("add.rn.bf16x2 %0, %1, %2;" : "=r"(d) : "r"(a), "r"(b)); return d; }
__device__ __forceinline__ uint32_t bf2_mul(uint32_t a, uint32_t b) { uint32_t d; asm("mul.rn.bf16x2 %0, %1, %2;" : "=r"(d) : "r"(a), "r"(b)); return d; }
__device__ __forceinline__ uint32_t nz(uint32_t w) { return w ? w : 0x80000000u; }
__device__ __forceinline__ uint32_t tg(float f) { return __float_as_uint(f) | 1u; }
__device__ __forceinline__ float uf(uint32_t w) { return __uint_as_float(w); }
__device__ __forceinline__ uint4 ldg128(const void* p) {
    uint4 v;
    asm volatile("ld.global.nc.L1::no_allocate.v4.u32 {%0,%1,%2,%3}, [%4];" : "=r"(v.x), "=r"(v.y), "=r"(v.z), "=r"(v.w) : "l"(p));
    return v;
}
__device__ __forceinline__ uint4 ldx128(const void* p) {
    uint4 v;
    asm volatile("ld.relaxed.gpu.global.v4.u32 {%0,%1,%2,%3}, [%4];" : "=r"(v.x), "=r"(v.y), "=r"(v.z), "=r"(v.w) : "l"(p) : "memory");
    return v;
}
__device__ __forceinline__ uint2 ldx64(const void* p) {
    uint2 v;
    asm volatile("ld.relaxed.gpu.global.v2.u32 {%0,%1}, [%2];" : "=r"(v.x), "=r"(v.y) : "l"(p) : "memory");
    return v;
}
__device__ __forceinline__ uint32_t ldx32(const void* p) {
    uint32_t v;
    asm volatile("ld.relaxed.gpu.global.u32 %0, [%1];" : "=r"(v) : "l"(p) : "memory");
    return v;
}
__device__ __forceinline__ void stx32(void* p, uint32_t v) { asm volatile("st.relaxed.gpu.global.u32 [%0], %1;" ::"l"(p), "r"(v) : "memory"); }
__device__ __forceinline__ void stx64(void* p, uint32_t a, uint32_t b) { asm volatile("st.relaxed.gpu.global.v2.u32 [%0], {%1,%2};" ::"l"(p), "r"(a), "r"(b) : "memory"); }
__device__ __forceinline__ void stx128(void* p, uint4 v) {
    asm volatile("st.relaxed.gpu.global.v4.u32 [%0], {%1,%2,%3,%4};" ::"l"(p), "r"(v.x), "r"(v.y), "r"(v.z), "r"(v.w) : "memory");
}
__device__ __forceinline__ bool ok4(const uint4& v) { return v.x && v.y && v.z && v.w; }
__device__ __forceinline__ uint32_t and4(const uint4& v) { return v.x & v.y & v.z & v.w; }

template <int N>
__device__ __forceinline__ void bfly(float* a, int lane, int off) {
    const bool up = (lane & off) != 0;
#pragma unroll
    for (int i = 0; i < N / 2; i++) {
        float send = up ? a[i] : a[i + N / 2];
        float keep = up ? a[i + N / 2] : a[i];
        a[i] = keep + __shfl_xor_sync(0xffffffffu, send, off);
    }
}
__device__ __forceinline__ void unpack8(const uint4& v, float* f) {
    f[0] = bf_lo(v.x); f[1] = bf_hi(v.x); f[2] = bf_lo(v.y); f[3] = bf_hi(v.y);
    f[4] = bf_lo(v.z); f[5] = bf_hi(v.z); f[6] = bf_lo(v.w); f[7] = bf_hi(v.w);
}
__device__ __forceinline__ void stats8(const float* v, float& mean, float& m2) {
    mean = (((v[0] + v[1]) + (v[2] + v[3])) + ((v[4] + v[5]) + (v[6] + v[7]))) * 0.125f;
    float a = 0.f, b = 0.f;
#pragma unroll
    for (int i = 0; i < 4; i++) {
        const float d0 = v[i] - mean, d1 = v[4 + i] - mean;
        a = fmaf(d0, d0, a); b = fmaf(d1, d1, b);
    }
    m2 = a + b;
}
__device__ __forceinline__ void stats_merge(float& mean, float& m2, int off, float half_n) {
    const float mo = __shfl_xor_sync(0xffffffffu, mean, off), qo = __shfl_xor_sync(0xffffffffu, m2, off);
    const float d = mean - mo;
    m2 = fmaf(d * d, half_n, m2 + qo);
    mean = 0.5f * (mean + mo);
}
__device__ __forceinline__ void ln_finish(float mean, float m2, uint32_t& mean2, float& inv_sd) {
    const float var = m2 * (1.0f / DM);
    mean2 = pack_bf16(mean, mean);
    inv_sd = rcp(rbf(sqrt_a(rbf(rbf(var) + 1e-5f))));
}
__device__ __forceinline__ uint32_t ln_mod2(uint32_t x2, uint32_t mean2, float inv_sd, uint32_t opc2, uint32_t sh2) {
    const uint32_t d = bf2_sub(x2, mean2);
    const uint32_t n = pack_bf16(bf_lo(d) * inv_sd, bf_hi(d) * inv_sd);
    return bf2_add(bf2_mul(n, opc2), sh2);
}
__device__ __forceinline__ uint4 make_record(float v, int lane, int grp) {
    const float vn = __shfl_down_sync(0xffffffffu, v, 1);
    const uint32_t w = nz(pack_bf16(v, vn));
    const int src = (lane & 3) * 8;
    uint4 r;
    r.x = __shfl_sync(0xffffffffu, w, src + 2 * ((0 + grp) & 3));
    r.y = __shfl_sync(0xffffffffu, w, src + 2 * ((1 + grp) & 3));
    r.z = __shfl_sync(0xffffffffu, w, src + 2 * ((2 + grp) & 3));
    r.w = __shfl_sync(0xffffffffu, w, src + 2 * ((3 + grp) & 3));
    return r;
}
__device__ __forceinline__ void fold_halves(const float* d0, const float* d1, int t, float* r) {
#pragma unroll
    for (int i = 0; i < 4; i++) {
        const float v = (t < 2) ? d0[i] : d1[i];
        r[i] = v + __shfl_xor_sync(0xffffffffu, v, 2);
    }
}

__global__ void __launch_bounds__(NTHREADS, 1)
fused_kernel(const __grid_constant__ CUtensorMap tmK, const __grid_constant__ CUtensorMap tmV,
             const __grid_constant__ CUtensorMap tmM, const __grid_constant__ CUtensorMap tmQ,
             const __grid_constant__ CUtensorMap tmWo, const __grid_constant__ CUtensorMap tmG,
             const __grid_constant__ CUtensorMap tmU, const __grid_constant__ CUtensorMap tmD,
             const bf16* __restrict__ x, const bf16* __restrict__ cvec, bf16* __restrict__ out) {
    extern __shared__ uint8_t smem_raw[];
    const uint32_t sbase = (smem_u32(smem_raw) + 1023u) & ~1023u;
    uint8_t* sptr = smem_raw + (sbase - smem_u32(smem_raw));
    const int tid = threadIdx.x, lane = tid & 31, warp = tid >> 5;
    const int cta = blockIdx.x;
    const int odd = cta & 1, cgrp = cta >> 1;
    const uint32_t bar_full = sbase + OFF_BAR, bar_empty = bar_full + NSLOT * 8;

    if (warp == 8) {
        if (lane < 2 * NSLOT) mbar_init(bar_full + lane * 8, lane < NSLOT ? 1 : 4);
        asm volatile("fence.mbarrier_init.release.cluster;" ::: "memory");
        __syncwarp();
        bar_arrive(3, 288);
        if (lane == 0) {
            uint64_t pol;
            asm volatile("createpolicy.fractional.L2::evict_first.b64 %0, 1.0;" : "=l"(pol));
            const int row0 = cta * (NTILE * TK);
            const int mcol = odd * (3 * DM) + cgrp * 8;
            if (!odd) {
                mbar_expect_tx(bar_full, SLOT);
#pragma unroll
                for (int i = 0; i < 4; i++) tma2d(sbase + i * 4096, &tmM, mcol + (i >> 1) * DM, (i & 1) * 256, bar_full);
            }
#pragma unroll
            for (int i = 1; i < 3; i++) {
                mbar_expect_tx(bar_full + i * 8, SLOT);
                tma2d(sbase + i * SLOT, &tmQ, cta * 32, (i - 1) * 256, bar_full + i * 8);
            }
#pragma unroll
            for (int i = 0; i < INFLIGHT; i++) {
                mbar_expect_tx(bar_full + (IT_KV + i) * 8, SLOT);
                tma3d_hint(sbase + (IT_KV + i) * SLOT, (i & 1) ? &tmV : &tmK, 0, row0 + (i >> 1) * TK, 0, bar_full + (IT_KV + i) * 8, pol);
            }
            if (odd) {
                mbar_expect_tx(bar_full, SLOT);
#pragma unroll
                for (int i = 0; i < 4; i++) tma2d(sbase + i * 4096, &tmM, mcol + (i >> 1) * DM, (i & 1) * 256, bar_full);
            }
            mbar_expect_tx(bar_full + 3 * 8, 8192);
            tma2d(sbase + 3 * SLOT, &tmM, mcol + 2 * DM, 0, bar_full + 3 * 8);
            tma2d(sbase + 3 * SLOT + 4096, &tmM, mcol + 2 * DM, 256, bar_full + 3 * 8);
            asm volatile("prefetch.tensormap [%0];" ::"l"(&tmWo) : "memory");
            asm volatile("prefetch.tensormap [%0];" ::"l"(&tmG) : "memory");
            asm volatile("prefetch.tensormap [%0];" ::"l"(&tmU) : "memory");
            asm volatile("prefetch.tensormap [%0];" ::"l"(&tmD) : "memory");
            const int nitems = IT_WO + ((cta < NFFN) ? 5 : 2);
            int slot = IT_KV + INFLIGHT, ph = 0;
            int wslot = IT_KV, wph = 0;
#pragma unroll 1
            for (int i = IT_KV + INFLIGHT; i < nitems; i++) {
                mbar_wait(bar_full + wslot * 8, wph);
                mbar_wait(bar_empty + slot * 8, ph ^ 1);
                const uint32_t dst = sbase + slot * SLOT, fb = bar_full + slot * 8;
                mbar_expect_tx(fb, SLOT);
                if (i < IT_WO) {
                    tma3d_hint(dst, (i & 1) ? &tmV : &tmK, 0, row0 + ((i - IT_KV) >> 1) * TK, 0, fb, pol);
                } else if (i < IT_WO + 2) {
                    tma2d(dst, &tmWo, (cta & 3) * 128 + (i - IT_WO) * 64, (cta >> 2) * 128, fb);
                } else if (i < IT_WO + 4) {
                    const CUtensorMap* m = (i == IT_WO + 2) ? &tmG : &tmU;
                    tma2d(dst, m, cta * 16, 0, fb);
                    tma2d(dst + 8192, m, cta * 16, 256, fb);
                } else {
                    tma3d(dst, &tmD, 0, cta * 16, 0, fb);
                }
                if (++slot == NSLOT) { slot = 0; ph ^= 1; }
                if (++wslot == NSLOT) { wslot = 0; wph ^= 1; }
            }
        }
        return;
    }

    float* s_red = reinterpret_cast<float*>(sptr + OFF_RED);
    float* s_red2 = reinterpret_cast<float*>(sptr + OFF_RED2);
    float* s_loc = reinterpret_cast<float*>(sptr + OFF_LOC);

    if (warp == 9) {
        const int ob = lane >> 3, oc = lane & 7;
        const float xown = __bfloat162float(x[ob * DM + cgrp * 8 + oc]);
        uint32_t mean2 = 0;
        float inv_sd = 0.f;
        if (!odd) {
            float mean = 0.f, m2 = 0.f;
            uint4 xv[8];
#pragma unroll
            for (int i = 0; i < 8; i++) xv[i] = ldg128(x + ob * DM + (i * 8 + oc) * 8);
#pragma unroll
            for (int i = 0; i < 8; i++) {
                float v[8], mi, qi;
                unpack8(xv[i], v);
                stats8(v, mi, qi);
                const float d = mi - mean;
                mean += d * (1.0f / (i + 1));
                m2 += qi + d * d * (8.0f * i / (i + 1));
            }
            stats_merge(mean, m2, 1, 32.f);
            stats_merge(mean, m2, 2, 64.f);
            stats_merge(mean, m2, 4, 128.f);
            ln_finish(mean, m2, mean2, inv_sd);
        }
        bar_sync(1, 288);
        float u0 = 0.f, u1 = 0.f;
#pragma unroll
        for (int w = 0; w < 8; w++) {
            u0 += s_red2[w * 96 + oc * 4 + ob];
            u1 += s_red2[w * 96 + 32 + oc * 4 + ob];
        }
        u0 = rbf(u0);
        u1 = rbf(1.0f + rbf(u1));
        if (!odd) {
            const float h = bf_hi(ln_mod2(__float_as_uint(xown), mean2, inv_sd, __float_as_uint(u1), __float_as_uint(u0)));
            const uint4 r = make_record(h, lane, cgrp);
            stx128(&g_hd.h[((lane >> 2) * 64 + cgrp) * 16 + (lane & 3) * 4], r);
            STAMPW(18);
        } else {
            const uint4 r0 = make_record(u0, lane, cgrp), r1 = make_record(u1, lane, cgrp);
            if (lane < 8) stx128(&g_hd.sbcb[((lane >> 2) * 64 + cgrp) * 16 + (lane & 3) * 4], (lane & 4) ? r1 : r0);
        }
        bar_sync(2, 288);
        {
            float u2 = 0.f;
#pragma unroll
            for (int w = 0; w < 8; w++) u2 += s_red2[w * 96 + 64 + oc * 4 + ob];
            s_loc[lane] = rbf(u2);
            s_loc[32 + lane] = xown;
        }
        {
            constexpr int N16 = sizeof(TailScratch) / 16 / NCTA;
            uint4* p = reinterpret_cast<uint4*>(&g_t) + (size_t)cta * N16;
            const uint4 z = make_uint4(0, 0, 0, 0);
#pragma unroll 1
            for (int i = lane; i < N16; i += 32) p[i] = z;
            __threadfence();
            __syncwarp();
            if (lane == 0) {
                atomicAdd(&g_cnt, 1u);
                unsigned it = 0;
                while (ldx32(&g_cnt) < (unsigned)NCTA && ++it < SPIN_LIMIT) __nanosleep(1000);
                __threadfence();
            }
            __syncwarp();
            STAMPW(17);
        }
        bar_arrive(4, 288);
        return;
    }

    const int g = lane >> 2, t = lane & 3;
    STAMP(0);
    int krel[2];
#pragma unroll
    for (int e = 0; e < 2; e++)
        krel[e] = warp * 64 + 8 * ((lane & 7) >> 1) + 2 * ((2 * e + (lane >> 4) + ((lane & 7) >> 1)) & 3) + (lane & 1);
    const int mch = (lane >> 3) & 1;
    const int rec_off = (warp * 8 + (g >> 2) * 4 + t) * 16 + (g & 3) * 4;

    {
        uint32_t cw[4];
        const uint32_t* cp = reinterpret_cast<const uint32_t*>(cvec) + (g & 3) * 256 + warp * 32 + ((g >> 2) * 4 + t) * 4;
#pragma unroll
        for (int s = 0; s < 4; s++) cw[s] = __ldg(cp + ((s + t) & 3));
#pragma unroll
        for (int s = 0; s < 4; s++) {
            const float a = bf_lo(cw[s]), b = bf_hi(cw[s]);
            cw[s] = pack_bf16(__fdividef(a, 1.0f + __expf(-a)), __fdividef(b, 1.0f + __expf(-b)));
        }
        bar_sync(3, 288);
        float d[2][4], r[4];
        STAMP(12);
        mbar_wait(bar_full, 0);
        if (!odd) STAMP(13);
#pragma unroll
        for (int hf = 0; hf < 2; hf++) {
            uint32_t a[2][4];
            ldsm4t(a[0], sbase + mch * 8192 + (krel[0] + hf * 32) * 16);
            ldsm4t(a[1], sbase + mch * 8192 + (krel[1] + hf * 32) * 16);
            mma16816z(d[hf], a[0], cw[0], cw[1]);
            mma16816(d[hf], a[1], cw[2], cw[3]);
        }
        fold_halves(d[0], d[1], t, r);
        if (t < 2) {
            *reinterpret_cast<float2*>(s_red2 + warp * 96 + g * 4 + 2 * t) = make_float2(r[0], r[1]);
            *reinterpret_cast<float2*>(s_red2 + warp * 96 + 32 + g * 4 + 2 * t) = make_float2(r[2], r[3]);
        }
        bar_arrive(1, 288);
        uint32_t af[2][2][2][4];
        mbar_wait(bar_full + (1 + (warp >> 2)) * 8, 0);
        STAMP(14);
#pragma unroll
        for (int hf = 0; hf < 2; hf++)
#pragma unroll
            for (int e = 0; e < 2; e++) {
                const int k = krel[e] + hf * 32;
#pragma unroll
                for (int mt = 0; mt < 2; mt++)
                    ldsm4t(af[hf][e][mt], sbase + SLOT + k * 64 + (((mt * 2 + mch) ^ ((k >> 1) & 3)) << 4));
            }
        uint4 hv;
        {
            const uint32_t* hp = g_hd.h + (cta & (NREP - 1)) * 1024 + rec_off;
            unsigned it = 0;
            hv = ldx128(hp);
            while (!ok4(hv) && ++it < SPIN_LIMIT) { __nanosleep(64); hv = ldx128(hp); }
        }
        __syncwarp();
        STAMP(15);
        float dq[2][2][4];
#pragma unroll
        for (int hf = 0; hf < 2; hf++)
#pragma unroll
            for (int mt = 0; mt < 2; mt++) {
                mma16816z(dq[hf][mt], af[hf][0][mt], hv.x, hv.y);
                mma16816(dq[hf][mt], af[hf][1][mt], hv.z, hv.w);
            }
#pragma unroll
        for (int mt = 0; mt < 2; mt++) {
            fold_halves(dq[0][mt], dq[1][mt], t, r);
            if (t < 2) {
                float* p = s_red + warp * 128 + 2 * t * 32 + mt * 16 + g;
                p[0] = r[0]; p[32] = r[1]; p[8] = r[2]; p[40] = r[3];
            }
        }
        bar_sync(5, 256);
        if (warp >= 4 && lane < 3) mbar_arrive(bar_empty + lane * 8);
        if (tid < 64) {
            const int b = tid >> 4, cp2 = tid & 15;
            float s0 = 0.f, s1 = 0.f;
#pragma unroll
            for (int w = 0; w < 8; w++) {
                float2 v = *reinterpret_cast<const float2*>(s_red + w * 128 + b * 32 + 2 * cp2);
                s0 += v.x; s1 += v.y;
            }
            stx32(&g_hd.q[b * (HQ * 64) + cta * 16 + cp2], nz(pack_bf16(s0, s1)));
        }
        STAMP(2);
        mbar_wait(bar_full + 3 * 8, 0);
#pragma unroll
        for (int hf = 0; hf < 2; hf++) {
            uint32_t a[2][4];
            ldsm4t(a[0], sbase + 3 * SLOT + (krel[0] + hf * 32) * 16);
            ldsm4t(a[1], sbase + 3 * SLOT + (krel[1] + hf * 32) * 16);
            mma16816z(d[hf], a[0], cw[0], cw[1]);
            mma16816(d[hf], a[1], cw[2], cw[3]);
        }
        fold_halves(d[0], d[1], t, r);
        if (t < 2) *reinterpret_cast<float2*>(s_red2 + warp * 96 + 64 + g * 4 + 2 * t) = make_float2(r[0], r[1]);
        bar_arrive(2, 288);
        STAMP(1);
    }

    const int pair = cta >> 2, split = cta & 3;
    const int ab = pair >> 3, kvh = pair & 7;
    uint32_t qf[4][4];
    {
        if (tid >= 64 && tid < 128) {
            const int i = tid - 64;
            const uint32_t* qp = g_hd.q + (ab * HQ + kvh * 4) * 64 + i * 4;
            unsigned it = 0;
            uint4 v = ldx128(qp);
            while (!ok4(v) && ++it < SPIN_LIMIT) { __nanosleep(64); v = ldx128(qp); }
            *reinterpret_cast<uint4*>(sptr + OFF_SO + (i >> 4) * 272 + (i & 15) * 16) = v;
        }
        bar_sync(5, 256);
        if (warp >= 4 && lane == 0) mbar_arrive(bar_empty + 3 * 8);
#pragma unroll
        for (int kp = 0; kp < 4; kp++) ldsm4(qf[kp], sbase + OFF_SO + (lane & 3) * 272 + kp * 64 + (lane >> 3) * 16);
    }
    STAMP(3);

    float o[8][4];
#pragma unroll
    for (int i = 0; i < 8; i++) { o[i][0] = o[i][1] = o[i][2] = o[i][3] = 0.f; }
    float m0 = -INFINITY, m1 = -INFINITY, l0 = 0.f, l1 = 0.f;
    {
        const int grp = warp >> 2, r0 = (warp & 3) * 16;
        const int krow = r0 + (lane & 7) + ((lane >> 3) & 1) * 8;
        const int vrow = r0 + (lane & 7) + (lane >> 4) * 8;
        const uint32_t koff = krow * 128, kx = krow & 7, kc = lane >> 4;
        const uint32_t voff = vrow * 128, vx = vrow & 7, vc = (lane >> 3) & 1;
        int slot = IT_KV + 2 * grp, ph = 0;
        const float scale = 0.08838834764831845f;
#pragma unroll 1
        for (int j = grp; j < NTILE; j += 2) {
            const uint32_t kb = sbase + slot * SLOT, vb = kb + SLOT;
            mbar_wait(bar_full + slot * 8, ph);
            float s[2][4];
#pragma unroll
            for (int ks = 0; ks < 8; ks++) {
                uint32_t a[4];
                ldsm4(a, kb + (ks >> 2) * 8192 + koff + ((((ks & 3) * 2 + kc) ^ kx) << 4));
                if (ks < 2) mma16816z(s[ks & 1], a, qf[ks >> 1][(ks & 1) * 2], qf[ks >> 1][(ks & 1) * 2 + 1]);
                else mma16816(s[ks & 1], a, qf[ks >> 1][(ks & 1) * 2], qf[ks >> 1][(ks & 1) * 2 + 1]);
            }
            __syncwarp();
            if (lane == 0) mbar_arrive(bar_empty + slot * 8);
            float sv[4];
#pragma unroll
            for (int i = 0; i < 4; i++) sv[i] = rbf(rbf(s[0][i] + s[1][i]) * scale);
            float t0 = fmaxf(sv[0], sv[2]), t1 = fmaxf(sv[1], sv[3]);
#pragma unroll
            for (int off = 4; off < 32; off <<= 1) {
                t0 = fmaxf(t0, __shfl_xor_sync(0xffffffffu, t0, off));
                t1 = fmaxf(t1, __shfl_xor_sync(0xffffffffu, t1, off));
            }
            const float n0 = fmaxf(m0, t0), n1 = fmaxf(m1, t1);
            if (__any_sync(0xffffffffu, (n0 != m0) || (n1 != m1))) {
                const float a0 = ex2((m0 - n0) * LOG2E), a1 = ex2((m1 - n1) * LOG2E);
                l0 *= a0; l1 *= a1;
#pragma unroll
                for (int i = 0; i < 8; i++) { o[i][0] *= a0; o[i][1] *= a1; o[i][2] *= a0; o[i][3] *= a1; }
                m0 = n0; m1 = n1;
            }
            const float p0 = ex2((sv[0] - m0) * LOG2E), p1 = ex2((sv[1] - m1) * LOG2E);
            const float p2 = ex2((sv[2] - m0) * LOG2E), p3 = ex2((sv[3] - m1) * LOG2E);
            l0 += p0 + p2; l1 += p1 + p3;
            const uint32_t b0 = movmat(pack_bf16(p0, p1)), b1 = movmat(pack_bf16(p2, p3));
            mbar_wait(bar_full + slot * 8 + 8, ph);
#pragma unroll
            for (int mt = 0; mt < 8; mt++) {
                uint32_t a[4];
                ldsm4t(a, vb + (mt >> 2) * 8192 + voff + ((((mt & 3) * 2 + vc) ^ vx) << 4));
                mma16816(o[mt], a, b0, b1);
            }
            __syncwarp();
            if (lane == 0) mbar_arrive(bar_empty + slot * 8 + 8);
            slot += 4;
            if (slot >= NSLOT) { slot -= NSLOT; ph ^= 1; }
        }
    }
    if (warp == 7) STAMPW(4);
    {
        float* s_mrg = reinterpret_cast<float*>(sptr + OFF_MRG);
        float* s_ml = reinterpret_cast<float*>(sptr + OFF_ML);
#pragma unroll
        for (int off = 4; off < 32; off <<= 1) {
            l0 += __shfl_xor_sync(0xffffffffu, l0, off);
            l1 += __shfl_xor_sync(0xffffffffu, l1, off);
        }
        if (t < 2) {
            float4* p0 = reinterpret_cast<float4*>(s_mrg + (warp * 4 + 2 * t) * MRG_H + g * MRG_G);
            float4* p1 = reinterpret_cast<float4*>(s_mrg + (warp * 4 + 2 * t + 1) * MRG_H + g * MRG_G);
#pragma unroll
            for (int i = 0; i < 4; i++) {
                p0[i] = make_float4(o[2 * i][0], o[2 * i][2], o[2 * i + 1][0], o[2 * i + 1][2]);
                p1[i] = make_float4(o[2 * i][1], o[2 * i][3], o[2 * i + 1][1], o[2 * i + 1][3]);
            }
            if (g == 0) *reinterpret_cast<float4*>(s_ml + (warp * 4 + 2 * t) * 2) = make_float4(m0, l0, m1, l1);
        }
        bar_sync(4, 288);
        const int hd = tid >> 6, dp = tid & 63;
        float mw[8], lw[8];
#pragma unroll
        for (int w = 0; w < 8; w++) {
            float2 v = *reinterpret_cast<const float2*>(s_ml + (w * 4 + hd) * 2);
            mw[w] = v.x; lw[w] = v.y;
        }
        const float M = fmaxf(fmaxf(fmaxf(mw[0], mw[1]), fmaxf(mw[2], mw[3])), fmaxf(fmaxf(mw[4], mw[5]), fmaxf(mw[6], mw[7])));
        float a0[2] = {0.f, 0.f}, a1[2] = {0.f, 0.f}, L[2] = {0.f, 0.f};
        const float* mp = s_mrg + hd * MRG_H + ((2 * dp) & 7) * MRG_G + (dp >> 2);
#pragma unroll
        for (int w = 0; w < 8; w++) {
            const float f = ex2((mw[w] - M) * LOG2E);
            a0[w & 1] = fmaf(f, mp[w * 4 * MRG_H], a0[w & 1]);
            a1[w & 1] = fmaf(f, mp[w * 4 * MRG_H + MRG_G], a1[w & 1]);
            L[w & 1] = fmaf(f, lw[w], L[w & 1]);
        }
        const int rec = ((kvh * 4 + hd) * NB + ab) * 4 + split;
        stx64(&g_t.po[rec * DH + 2 * dp], tg(a0[0] + a0[1]), tg(a1[0] + a1[1]));
        if (dp == 0) stx64(&g_t.pml[rec * 2], tg(M), tg(L[0] + L[1]));
    }
    STAMP(5);
    uint4 sbv, cbv;
    {
        const int hh = cta >> 2;
        const int b = tid >> 6, dp = tid & 63;
        const uint32_t* op = g_t.po + (hh * NB + b) * 4 * DH + 2 * dp;
        const uint32_t* mp = g_t.pml + (hh * NB + b) * 8;
        unsigned it = 0;
        do {
            sbv = ldx128(g_hd.sbcb + rec_off);
            cbv = ldx128(g_hd.sbcb + 1024 + rec_off);
        } while (!(ok4(sbv) && ok4(cbv)) && ++it < SPIN_LIMIT);
        uint2 v[4];
        uint4 ml0, ml1;
        uint32_t okw;
        do {
#pragma unroll
            for (int s = 0; s < 4; s++) v[s] = ldx64(op + s * DH);
            ml0 = ldx128(mp);
            ml1 = ldx128(mp + 4);
            okw = and4(ml0) & and4(ml1) & (v[0].x & v[0].y & v[1].x) & (v[1].y & v[2].x & v[2].y) & (v[3].x & v[3].y);
        } while (!(okw & 1) && ++it < SPIN_LIMIT);
        const float M = fmaxf(fmaxf(uf(ml0.x), uf(ml0.z)), fmaxf(uf(ml1.x), uf(ml1.z)));
        const float f0 = ex2((uf(ml0.x) - M) * LOG2E), f1 = ex2((uf(ml0.z) - M) * LOG2E);
        const float f2 = ex2((uf(ml1.x) - M) * LOG2E), f3 = ex2((uf(ml1.z) - M) * LOG2E);
        const float inv = rcp(fmaf(f0, uf(ml0.y), f1 * uf(ml0.w)) + fmaf(f2, uf(ml1.y), f3 * uf(ml1.w)));
        const float o0 = fmaf(f0, uf(v[0].x), f1 * uf(v[1].x)) + fmaf(f2, uf(v[2].x), f3 * uf(v[3].x));
        const float o1 = fmaf(f0, uf(v[0].y), f1 * uf(v[1].y)) + fmaf(f2, uf(v[2].y), f3 * uf(v[3].y));
        *reinterpret_cast<uint32_t*>(sptr + OFF_SO + b * 272 + dp * 4) = pack_bf16(o0 * inv, o1 * inv);
        __syncwarp();
        STAMP(6);
        static_assert(slot_of(IT_WO) + 1 == slot_of(IT_WO + 1) && phase_of(IT_WO) == phase_of(IT_WO + 1), "wo items");
        const int half = warp >> 2;
        mbar_wait(bar_full + (slot_of(IT_WO) + half) * 8, phase_of(IT_WO));
        STAMP(21);
        uint32_t af[8][4];
        {
            const uint32_t wb = sbase + (slot_of(IT_WO) + half) * SLOT;
            const int krow = (lane & 7) + (lane >> 4) * 8;
            const uint32_t ch = (warp & 3) * 2 + mch;
#pragma unroll
            for (int ks = 0; ks < 8; ks++) ldsm4t(af[ks], wb + (ks * 16 + krow) * 128 + ((ch ^ (krow & 7)) << 4));
        }
        bar_sync(5, 256);
        float d[4][4];
        uint32_t bf[4][4];
#pragma unroll
        for (int kp = 0; kp < 4; kp++) ldsm4(bf[kp], sbase + OFF_SO + (lane & 3) * 272 + kp * 64 + (lane >> 3) * 16);
#pragma unroll
        for (int kp = 0; kp < 4; kp++) mma16816z(d[kp], af[2 * kp], bf[kp][0], bf[kp][1]);
#pragma unroll
        for (int kp = 0; kp < 4; kp++) mma16816(d[kp], af[2 * kp + 1], bf[kp][2], bf[kp][3]);
        if (t < 2) {
            uint32_t* p = g_t.wop + (((cta & 3) * 16 + warp * 2) * HQ + hh) * 32 + g * 4 + 2 * t;
            stx64(p, tg((d[0][0] + d[1][0]) + (d[2][0] + d[3][0])), tg((d[0][1] + d[1][1]) + (d[2][1] + d[3][1])));
            stx64(p + HQ * 32, tg((d[0][2] + d[1][2]) + (d[2][2] + d[3][2])), tg((d[0][3] + d[1][3]) + (d[2][3] + d[3][3])));
        }
    }
    STAMP(7);
    if (!odd && warp == 0) {
        const uint32_t* p = g_t.wop + cgrp * (HQ * 32) + lane * 4;
        const float gav = s_loc[lane], xo = s_loc[32 + lane];
        uint4 v[8];
        unsigned it = 0;
        uint32_t okw;
        do {
#pragma unroll
            for (int i = 0; i < 8; i++) v[i] = ldx128(p + i * 128);
            okw = (and4(v[0]) & and4(v[1])) & (and4(v[2]) & and4(v[3])) & (and4(v[4]) & and4(v[5])) & (and4(v[6]) & and4(v[7]));
        } while (!(okw & 1) && ++it < SPIN_LIMIT);
        __syncwarp();
        STAMP(25);
        float a[4];
        a[0] = ((uf(v[0].x) + uf(v[1].x)) + (uf(v[2].x) + uf(v[3].x))) + ((uf(v[4].x) + uf(v[5].x)) + (uf(v[6].x) + uf(v[7].x)));
        a[1] = ((uf(v[0].y) + uf(v[1].y)) + (uf(v[2].y) + uf(v[3].y))) + ((uf(v[4].y) + uf(v[5].y)) + (uf(v[6].y) + uf(v[7].y)));
        a[2] = ((uf(v[0].z) + uf(v[1].z)) + (uf(v[2].z) + uf(v[3].z))) + ((uf(v[4].z) + uf(v[5].z)) + (uf(v[6].z) + uf(v[7].z)));
        a[3] = ((uf(v[0].w) + uf(v[1].w)) + (uf(v[2].w) + uf(v[3].w))) + ((uf(v[4].w) + uf(v[5].w)) + (uf(v[6].w) + uf(v[7].w)));
        bfly<4>(a, lane, 16);
        bfly<2>(a, lane, 8);
        const float x1 = xo + rbf(gav * rbf(a[0]));
        const uint4 r = make_record(x1, lane, cgrp);
        stx128(&g_t.x1[((lane >> 2) * 64 + cgrp) * 16 + (lane & 3) * 4], r);
        STAMP(8);
    }
    if (cta < NFFN) {
        constexpr int SG = slot_of(IT_WO + 2), SU = slot_of(IT_WO + 3), SD = slot_of(IT_WO + 4);
        uint32_t ag[2][2][4], au[2][2][4];
        mbar_wait(bar_full + SG * 8, phase_of(IT_WO + 2));
        mbar_wait(bar_full + SU * 8, phase_of(IT_WO + 3));
        if (warp == 1) STAMPW(22);
#pragma unroll
        for (int hf = 0; hf < 2; hf++)
#pragma unroll
            for (int e = 0; e < 2; e++) {
                const int k = krel[e] + hf * 32;
                const uint32_t off = k * 32 + ((mch ^ ((k >> 2) & 1)) << 4);
                ldsm4t(ag[hf][e], sbase + SG * SLOT + off);
                ldsm4t(au[hf][e], sbase + SU * SLOT + off);
            }
        uint32_t ad[4][4];
        {
            mbar_wait(bar_full + SD * 8, phase_of(IT_WO + 4));
            if (warp == 1) STAMPW(24);
            const int krow = (lane & 7) + (lane >> 4) * 8;
#pragma unroll
            for (int mt = 0; mt < 4; mt++) {
                const uint32_t ch = mt * 2 + mch;
                ldsm4t(ad[mt], sbase + SD * SLOT + warp * 2048 + krow * 128 + ((ch ^ (krow & 7)) << 4));
            }
        }
        uint32_t hw[4];
        {
            const uint32_t* p = g_t.x1 + (cta & (NREP - 1)) * 1024 + rec_off;
            unsigned it = 0;
            uint4 xv = ldx128(p);
            while (!ok4(xv) && ++it < SPIN_LIMIT) { __nanosleep(40); xv = ldx128(p); }
            __syncwarp();
            STAMP(23);
            float v[8], mean, m2;
            unpack8(xv, v);
            stats8(v, mean, m2);
            stats_merge(mean, m2, 1, 4.f);
            stats_merge(mean, m2, 2, 8.f);
            stats_merge(mean, m2, 16, 16.f);
            float2* st = reinterpret_cast<float2*>(sptr + OFF_ST);
            if (t == 0 && g < 4) st[g * 8 + warp] = make_float2(mean, m2);
            bar_sync(5, 256);
            float4 pw[4];
#pragma unroll
            for (int i = 0; i < 4; i++) pw[i] = reinterpret_cast<const float4*>(st + (g & 3) * 8)[i];
            mean = (((pw[0].x + pw[0].z) + (pw[1].x + pw[1].z)) + ((pw[2].x + pw[2].z) + (pw[3].x + pw[3].z))) * 0.125f;
            m2 = ((pw[0].y + pw[0].w) + (pw[1].y + pw[1].w)) + ((pw[2].y + pw[2].w) + (pw[3].y + pw[3].w));
            float dv0 = 0.f, dv1 = 0.f;
#pragma unroll
            for (int i = 0; i < 4; i++) {
                const float d0 = pw[i].x - mean, d1 = pw[i].z - mean;
                dv0 = fmaf(d0, d0, dv0); dv1 = fmaf(d1, d1, dv1);
            }
            uint32_t mean2;
            float inv_sd;
            ln_finish(mean, fmaf(dv0 + dv1, 64.0f, m2), mean2, inv_sd);
            hw[0] = ln_mod2(xv.x, mean2, inv_sd, cbv.x, sbv.x);
            hw[1] = ln_mod2(xv.y, mean2, inv_sd, cbv.y, sbv.y);
            hw[2] = ln_mod2(xv.z, mean2, inv_sd, cbv.z, sbv.z);
            hw[3] = ln_mod2(xv.w, mean2, inv_sd, cbv.w, sbv.w);
        }
        STAMP(9);
        {
            float dg[2][4], du[2][4], rg[4], ru[4];
#pragma unroll
            for (int hf = 0; hf < 2; hf++) {
                mma16816z(dg[hf], ag[hf][0], hw[0], hw[1]);
                mma16816z(du[hf], au[hf][0], hw[0], hw[1]);
            }
#pragma unroll
            for (int hf = 0; hf < 2; hf++) {
                mma16816(dg[hf], ag[hf][1], hw[2], hw[3]);
                mma16816(du[hf], au[hf][1], hw[2], hw[3]);
            }
            fold_halves(dg[0], dg[1], t, rg);
            fold_halves(du[0], du[1], t, ru);
            float* p = s_red + warp * 128 + g * 8 + (t & 1) * 4 + (t >> 1) * 64;
            *reinterpret_cast<float4*>(p) = (t < 2) ? make_float4(rg[0], ru[0], rg[1], ru[1]) : make_float4(rg[2], ru[2], rg[3], ru[3]);
        }
        bar_sync(5, 256);
        if (tid < 64) {
            float2 v[8];
#pragma unroll
            for (int w = 0; w < 8; w++) v[w] = *reinterpret_cast<const float2*>(s_red + w * 128 + tid * 2);
            const float gv = rbf(((v[0].x + v[1].x) + (v[2].x + v[3].x)) + ((v[4].x + v[5].x) + (v[6].x + v[7].x)));
            const float uv = rbf(((v[0].y + v[1].y) + (v[2].y + v[3].y)) + ((v[4].y + v[5].y) + (v[6].y + v[7].y)));
            const float inner = 0.7978845608028654f * (gv + 0.044715f * gv * gv * gv);
            const float th = 1.0f - 2.0f * rcp(ex2(inner * (2.0f * LOG2E)) + 1.0f);
            const float ge = rbf(0.5f * gv * (1.0f + th));
            const int col = tid >> 2, b = tid & 3;
            *reinterpret_cast<bf16*>(sptr + OFF_ACT + b * 48 + col * 2) = __float2bfloat16_rn(ge * uv);
        } else if (cta < 72 && tid >= 192) {
            reinterpret_cast<uint4*>(&g_hd)[cta * 64 + tid - 192] = make_uint4(0, 0, 0, 0);
        }
        bar_sync(5, 256);
        {
            uint32_t bf[2];
            ldsm2(bf, sbase + OFF_ACT + (lane & 3) * 48 + mch * 16);
            uint32_t* p = g_t.dnp + ((warp * 8 + (t >> 1)) * NFFN + cta) * 32 + g * 4 + 2 * (t & 1);
#pragma unroll
            for (int mt = 0; mt < 4; mt++) {
                float d[4];
                mma16816z(d, ad[mt], bf[0], bf[1]);
                stx64(p + (2 * mt) * (NFFN * 32), tg(t < 2 ? d[0] : d[2]), tg(t < 2 ? d[1] : d[3]));
            }
        }
        STAMP(10);
    }
    if (odd) {
        const uint32_t* p = g_t.dnp + cgrp * (NFFN * 32) + tid * 4;
        uint32_t x1w = 1;
        unsigned it = 0;
        if (warp == 0) {
            const uint32_t* xp = g_t.x1 + cgrp * 16 + (lane >> 3) * 4 + ((((lane & 7) >> 1) - cgrp) & 3);
            x1w = ldx32(xp);
            while (!x1w && ++it < SPIN_LIMIT) { __nanosleep(100); x1w = ldx32(xp); }
        }
        uint4 v[4];
        v[3] = make_uint4(1u, 1u, 1u, 1u);
        uint32_t okw;
        do {
            v[0] = ldx128(p);
            v[1] = ldx128(p + 1024);
            v[2] = ldx128(p + 2048);
            if (tid < 128) v[3] = ldx128(p + 3072);
            okw = (and4(v[0]) & and4(v[1])) & (and4(v[2]) & and4(v[3]));
        } while (!(okw & 1) && ++it < SPIN_LIMIT);
        __syncwarp();
        STAMP(26);
        float a[4];
        a[0] = (uf(v[0].x) + uf(v[1].x)) + (uf(v[2].x) + uf(v[3].x));
        a[1] = (uf(v[0].y) + uf(v[1].y)) + (uf(v[2].y) + uf(v[3].y));
        a[2] = (uf(v[0].z) + uf(v[1].z)) + (uf(v[2].z) + uf(v[3].z));
        a[3] = (uf(v[0].w) + uf(v[1].w)) + (uf(v[2].w) + uf(v[3].w));
        bfly<4>(a, lane, 16);
        bfly<2>(a, lane, 8);
        s_red2[warp * 32 + lane] = a[0];
        bar_sync(5, 256);
        if (warp == 0) {
            float f[8];
#pragma unroll
            for (int w = 0; w < 8; w++) f[w] = s_red2[w * 32 + lane];
            const float ffn = ((f[0] + f[1]) + (f[2] + f[3])) + ((f[4] + f[5]) + (f[6] + f[7]));
            const float x1 = (lane & 1) ? bf_hi(x1w) : bf_lo(x1w);
            const float r = x1 + rbf(s_loc[lane] * rbf(ffn));
            out[(lane >> 3) * DM + cgrp * 8 + (lane & 7)] = __float2bfloat16_rn(r);
            if (cta == 1 && lane == 0) g_cnt = 0;
        }
        STAMP(11);
    }
}

typedef CUresult (*EncodeFn)(CUtensorMap*, CUtensorMapDataType, cuuint32_t, void*, const cuuint64_t*, const cuuint64_t*,
                             const cuuint32_t*, const cuuint32_t*, CUtensorMapInterleave, CUtensorMapSwizzle,
                             CUtensorMapL2promotion, CUtensorMapFloatOOBfill);

void encode(EncodeFn fn, CUtensorMap* m, const void* base, int rank, const cuuint64_t* dims, const cuuint64_t* strides,
            const cuuint32_t* box, CUtensorMapSwizzle sw, CUtensorMapL2promotion promo) {
    cuuint32_t es[3] = {1, 1, 1};
    fn(m, CU_TENSOR_MAP_DATA_TYPE_BFLOAT16, rank, const_cast<void*>(base), dims, strides, box, es,
       CU_TENSOR_MAP_INTERLEAVE_NONE, sw, promo, CU_TENSOR_MAP_FLOAT_OOB_FILL_NONE);
}

}

extern "C" void kernel_launch(void* const* d_in, const int* in_sizes, int n_in, void* d_out, int out_size) {
    (void)in_sizes; (void)n_in; (void)out_size;
    const bf16* x = (const bf16*)d_in[0];
    const bf16* kc = (const bf16*)d_in[1];
    const bf16* vc = (const bf16*)d_in[2];
    const bf16* wq = (const bf16*)d_in[3];
    const bf16* wo = (const bf16*)d_in[4];
    const bf16* wg = (const bf16*)d_in[6];
    const bf16* wu = (const bf16*)d_in[7];
    const bf16* wd = (const bf16*)d_in[8];
    const bf16* cv = (const bf16*)d_in[9];
    const bf16* wm = (const bf16*)d_in[10];

    static EncodeFn fn = nullptr;
    if (!fn) {
        void* p = nullptr;
        cudaDriverEntryPointQueryResult st;
        cudaGetDriverEntryPoint("cuTensorMapEncodeTiled", &p, cudaEnableDefault, &st);
        fn = (EncodeFn)p;
        cudaFuncSetAttribute(fused_kernel, cudaFuncAttributeMaxDynamicSharedMemorySize, SMEM_BYTES);
    }
    CUtensorMap tmK, tmV, tmM, tmQ, tmWo, tmG, tmU, tmD;
    {
        cuuint64_t dims[2] = {6 * DM, DM};
        cuuint64_t strides[1] = {6 * DM * 2};
        cuuint32_t box[2] = {8, 256};
        encode(fn, &tmM, wm, 2, dims, strides, box, CU_TENSOR_MAP_SWIZZLE_NONE, CU_TENSOR_MAP_L2_PROMOTION_L2_128B);
    }
    {
        cuuint64_t dims[2] = {HQ * DH, DM};
        cuuint64_t strides[1] = {HQ * DH * 2};
        cuuint32_t box[2] = {32, 256};
        encode(fn, &tmQ, wq, 2, dims, strides, box, CU_TENSOR_MAP_SWIZZLE_64B, CU_TENSOR_MAP_L2_PROMOTION_L2_128B);
    }
    {
        cuuint64_t dims[3] = {64, (cuuint64_t)NB * HKV * SK, 2};
        cuuint64_t strides[2] = {256, 128};
        cuuint32_t box[3] = {64, TK, 2};
        encode(fn, &tmK, kc, 3, dims, strides, box, CU_TENSOR_MAP_SWIZZLE_128B, CU_TENSOR_MAP_L2_PROMOTION_L2_256B);
        encode(fn, &tmV, vc, 3, dims, strides, box, CU_TENSOR_MAP_SWIZZLE_128B, CU_TENSOR_MAP_L2_PROMOTION_L2_256B);
    }
    {
        cuuint64_t dims[2] = {DM, HQ * DH};
        cuuint64_t strides[1] = {DM * 2};
        cuuint32_t box[2] = {64, 128};
        encode(fn, &tmWo, wo, 2, dims, strides, box, CU_TENSOR_MAP_SWIZZLE_128B, CU_TENSOR_MAP_L2_PROMOTION_L2_256B);
    }
    {
        cuuint64_t dims[2] = {FF, DM};
        cuuint64_t strides[1] = {FF * 2};
        cuuint32_t box[2] = {16, 256};
        encode(fn, &tmG, wg, 2, dims, strides, box, CU_TENSOR_MAP_SWIZZLE_32B, CU_TENSOR_MAP_L2_PROMOTION_L2_128B);
        encode(fn, &tmU, wu, 2, dims, strides, box, CU_TENSOR_MAP_SWIZZLE_32B, CU_TENSOR_MAP_L2_PROMOTION_L2_128B);
    }
    {
        cuuint64_t dims[3] = {64, FF, 8};
        cuuint64_t strides[2] = {DM * 2, 128};
        cuuint32_t box[3] = {64, 16, 8};
        encode(fn, &tmD, wd, 3, dims, strides, box, CU_TENSOR_MAP_SWIZZLE_128B, CU_TENSOR_MAP_L2_PROMOTION_L2_256B);
    }
    fused_kernel<<<NCTA, NTHREADS, SMEM_BYTES>>>(tmK, tmV, tmM, tmQ, tmWo, tmG, tmU, tmD, x, cv, (bf16*)d_out);
}
```

```cpp
#include <cuda_runtime.h>
#include <cuda_bf16.h>
#include <cuda.h>
#include <stdint.h>

typedef __nv_bfloat16 bf16;

namespace {

constexpr int NB = 4, DM = 512, HQ = 32, HKV = 8, SK = 8192, DH = 128, FF = 1792;
constexpr int NCTA = 128;
constexpr int NSLOT = 8;
constexpr int SLOT = 16384;
constexpr int TK = 64;
constexpr int NTILE = 32;
constexpr int NKV = 2 * NTILE;
constexpr int INFLIGHT = 4;
constexpr int WIN0 = 2;
constexpr int XS = 2;
constexpr int DEFER0 = 14;
constexpr int PACE_LO = 128, PACE_HI = 320, PACE_BIAS = 64;
constexpr int WWIN = 3;
constexpr int LEAD0 = 48;
constexpr unsigned SCDELAY = 2500, QDELAY = 2500, H1DELAY = 900, H2DELAY = 500, H2DUAL = 300, H3DELAY = 2400, H4DELAY = 500;
constexpr int NWBOX = 10;
constexpr int NFFN = FF / 16;
constexpr int NREP = 8;
constexpr int NTHREADS = 352;
constexpr unsigned SPIN_LIMIT = 1u << 17;
constexpr float LOG2E = 1.4426950408889634f;

struct __align__(128) TailScratch {
    uint32_t po[HQ * NB * 4 * DH];
    uint32_t pml[HQ * NB * 4 * 2];
    uint32_t wop[64 * HQ * 32];
    uint32_t x1[NREP * 64 * 16];
    uint32_t dnp[64 * NFFN * 32];
};
static_assert(sizeof(TailScratch) % (NCTA * 16) == 0, "scratch must split evenly");
struct __align__(128) HeadScratch {
    uint32_t sc[2 * NREP * 64 * 16];
    uint32_t q[NB * HQ * 64];
    uint32_t sbcb[2 * 64 * 16];
};
static_assert(sizeof(HeadScratch) == 104 * 1024, "head scratch is cleared by 104 CTAs x 1 KB");
__device__ TailScratch g_t;
__device__ HeadScratch g_hd;
__device__ unsigned g_prog;
__device__ unsigned g_cnt;

constexpr int MRG_G = 20, MRG_H = 8 * MRG_G + 4;
constexpr int OFF_W = NSLOT * SLOT;
constexpr int OFF_WQ = OFF_W + 8192, OFF_WM = OFF_W + 40960;
constexpr int OFF_ML = OFF_W + 5 * SLOT;
constexpr int OFF_RED = OFF_ML + 8 * 4 * 2 * 4;
constexpr int OFF_RED2 = OFF_RED + 8 * 128 * 4;
constexpr int OFF_CW = OFF_RED2 + 8 * 32 * 4;
constexpr int OFF_SO = OFF_CW + 8 * 32 * 16;
constexpr int OFF_ST = OFF_SO + 4 * 136 * 2;
constexpr int OFF_ACT = OFF_ST + 8 * 4 * 8;
constexpr int OFF_LOC = OFF_ACT + 4 * 24 * 2;
constexpr int OFF_PACE = OFF_LOC + 64 * 4;
constexpr int OFF_BAR = OFF_PACE + 16;
constexpr int NSB = NSLOT + XS;
constexpr int OFF_X = OFF_WM;
constexpr int NBAR = 2 * NSB + NWBOX + 5;
constexpr int SMEM_USED = OFF_BAR + NBAR * 8;
constexpr int SMEM_BYTES = SMEM_USED + 1024;
static_assert(SMEM_BYTES <= 232448, "too much smem");
static_assert(OFF_BAR % 8 == 0 && OFF_SO % 16 == 0 && OFF_ST % 16 == 0 && OFF_ACT % 16 == 0 && OFF_ML % 16 == 0 && OFF_CW % 16 == 0, "align");

__host__ __device__ constexpr int item_at(int pos) { return (pos <= LEAD0 || pos == NKV - 1) ? pos : ((pos & 1) ? pos + 1 : pos - 1); }

__host__ __device__ constexpr int bar_of(int k) { return k < NSB ? k : ((k - XS) & 7); }
__host__ __device__ constexpr int lap_of(int k) { return k < NSB ? 0 : ((k - XS) >> 3); }
__host__ __device__ constexpr int off_of(int k) { return (k >= 8 && k < NSB) ? OFF_X + (k - 8) * SLOT : bar_of(k) * SLOT; }

__device__ __forceinline__ uint32_t smem_u32(const void* p) { return (uint32_t)__cvta_generic_to_shared(p); }
__device__ __forceinline__ void mbar_init(uint32_t bar, int cnt) { asm volatile("mbarrier.init.shared::cta.b64 [%0], %1;" ::"r"(bar), "r"(cnt) : "memory"); }
__device__ __forceinline__ void mbar_expect_tx(uint32_t bar, uint32_t bytes) { asm volatile("mbarrier.arrive.expect_tx.shared::cta.b64 _, [%0], %1;" ::"r"(bar), "r"(bytes) : "memory"); }
__device__ __forceinline__ void mbar_arrive(uint32_t bar) { asm volatile("mbarrier.arrive.shared::cta.b64 _, [%0];" ::"r"(bar) : "memory"); }
__device__ __forceinline__ bool mbar_try(uint32_t bar, uint32_t parity) {
    uint32_t ok;
    asm volatile("{\n.reg .pred p;\nmbarrier.try_wait.parity.shared::cta.b64 p, [%1], %2;\nselp.u32 %0, 1, 0, p;\n}" : "=r"(ok) : "r"(bar), "r"(parity) : "memory");
    return ok != 0;
}
__device__ __forceinline__ bool mbar_test(uint32_t bar, uint32_t parity) {
    uint32_t ok;
    asm volatile("{\n.reg .pred p;\nmbarrier.test_wait.parity.shared::cta.b64 p, [%1], %2;\nselp.u32 %0, 1, 0, p;\n}" : "=r"(ok) : "r"(bar), "r"(parity) : "memory");
    return ok != 0;
}
__device__ __forceinline__ void mbar_wait(uint32_t bar, uint32_t parity) {
    if (mbar_try(bar, parity)) return;
    unsigned t0, t1;
    asm volatile("mov.u32 %0, %clock;" : "=r"(t0));
#pragma unroll 1
    while (!mbar_try(bar, parity)) {
        asm volatile("mov.u32 %0, %clock;" : "=r"(t1));
        if (t1 - t0 > (1u << 26)) break;
    }
}
__device__ __forceinline__ void tma2d(uint32_t dst, const CUtensorMap* m, int c0, int c1, uint32_t bar) {
    asm volatile("cp.async.bulk.tensor.2d.shared::cluster.global.mbarrier::complete_tx::bytes [%0], [%1, {%3, %4}], [%2];" ::"r"(dst), "l"(m), "r"(bar), "r"(c0), "r"(c1) : "memory");
}
__device__ __forceinline__ void tma3d(uint32_t dst, const CUtensorMap* m, int c0, int c1, int c2, uint32_t bar) {
    asm volatile("cp.async.bulk.tensor.3d.shared::cluster.global.mbarrier::complete_tx::bytes [%0], [%1, {%3, %4, %5}], [%2];" ::"r"(dst), "l"(m), "r"(bar), "r"(c0), "r"(c1), "r"(c2) : "memory");
}
__device__ __forceinline__ void tma3d_hint(uint32_t dst, const CUtensorMap* m, int c0, int c1, int c2, uint32_t bar, uint64_t pol) {
    asm volatile("cp.async.bulk.tensor.3d.shared::cluster.global.mbarrier::complete_tx::bytes.L2::cache_hint [%0], [%1, {%3, %4, %5}], [%2], %6;" ::"r"(dst), "l"(m), "r"(bar), "r"(c0), "r"(c1), "r"(c2), "l"(pol) : "memory");
}
__device__ __forceinline__ void bar_sync(int id, int n) { asm volatile("bar.sync %0, %1;" ::"r"(id), "r"(n) : "memory"); }
__device__ __forceinline__ void bar_arrive(int id, int n) { asm volatile("bar.arrive %0, %1;" ::"r"(id), "r"(n) : "memory"); }
__device__ __forceinline__ void ldsm4(uint32_t* r, uint32_t addr) {
    asm volatile("ldmatrix.sync.aligned.m8n8.x4.shared.b16 {%0,%1,%2,%3}, [%4];" : "=r"(r[0]), "=r"(r[1]), "=r"(r[2]), "=r"(r[3]) : "r"(addr) : "memory");
}
__device__ __forceinline__ void ldsm4t(uint32_t* r, uint32_t addr) {
    asm volatile("ldmatrix.sync.aligned.m8n8.x4.trans.shared.b16 {%0,%1,%2,%3}, [%4];" : "=r"(r[0]), "=r"(r[1]), "=r"(r[2]), "=r"(r[3]) : "r"(addr) : "memory");
}
__device__ __forceinline__ void ldsm2(uint32_t* r, uint32_t addr) {
    asm volatile("ldmatrix.sync.aligned.m8n8.x2.shared.b16 {%0,%1}, [%2];" : "=r"(r[0]), "=r"(r[1]) : "r"(addr) : "memory");
}
__device__ __forceinline__ void mma16816(float* d, const uint32_t* a, uint32_t b0, uint32_t b1) {
    asm volatile("mma.sync.aligned.m16n8k16.row.col.f32.bf16.bf16.f32 {%0,%1,%2,%3}, {%4,%5,%6,%7}, {%8,%9}, {%0,%1,%2,%3};"
                 : "+f"(d[0]), "+f"(d[1]), "+f"(d[2]), "+f"(d[3]) : "r"(a[0]), "r"(a[1]), "r"(a[2]), "r"(a[3]), "r"(b0), "r"(b1));
}
__device__ __forceinline__ void mma16816z(float* d, const uint32_t* a, uint32_t b0, uint32_t b1) {
    asm volatile("mma.sync.aligned.m16n8k16.row.col.f32.bf16.bf16.f32 {%0,%1,%2,%3}, {%4,%5,%6,%7}, {%8,%9}, {%10,%10,%10,%10};"
                 : "=f"(d[0]), "=f"(d[1]), "=f"(d[2]), "=f"(d[3]) : "r"(a[0]), "r"(a[1]), "r"(a[2]), "r"(a[3]), "r"(b0), "r"(b1), "f"(0.f));
}
__device__ __forceinline__ uint32_t movmat(uint32_t a) {
    uint32_t d;
    asm volatile("movmatrix.sync.aligned.m8n8.trans.b16 %0, %1;" : "=r"(d) : "r"(a));
    return d;
}
__device__ __forceinline__ uint32_t pack_bf16(float lo, float hi) {
    uint32_t r;
    asm("cvt.rn.bf16x2.f32 %0, %1, %2;" : "=r"(r) : "f"(hi), "f"(lo));
    return r;
}
__device__ __forceinline__ float bf_lo(uint32_t w) { return __uint_as_float(w << 16); }
__device__ __forceinline__ float bf_hi(uint32_t w) { return __uint_as_float(w & 0xffff0000u); }
__device__ __forceinline__ float rbf(float x) { return __uint_as_float(pack_bf16(0.f, x)); }
__device__ __forceinline__ float ex2(float x) { float y; asm("ex2.approx.ftz.f32 %0, %1;" : "=f"(y) : "f"(x)); return y; }
__device__ __forceinline__ float rcp(float x) { float y; asm("rcp.approx.ftz.f32 %0, %1;" : "=f"(y) : "f"(x)); return y; }
__device__ __forceinline__ float sqrt_a(float x) { float y; asm("sqrt.approx.ftz.f32 %0, %1;" : "=f"(y) : "f"(x)); return y; }
__device__ __forceinline__ uint32_t bf2_sub(uint32_t a, uint32_t b) { uint32_t d; asm("sub.rn.bf16x2 %0, %1, %2;" : "=r"(d) : "r"(a), "r"(b)); return d; }
__device__ __forceinline__ uint32_t bf2_add(uint32_t a, uint32_t b) { uint32_t d; asm("add.rn.bf16x2 %0, %1, %2;" : "=r"(d) : "r"(a), "r"(b)); return d; }
__device__ __forceinline__ uint32_t bf2_mul(uint32_t a, uint32_t b) { uint32_t d; asm("mul.rn.bf16x2 %0, %1, %2;" : "=r"(d) : "r"(a), "r"(b)); return d; }
__device__ __forceinline__ uint32_t nz(uint32_t w) { return w ? w : 0x80000000u; }
__device__ __forceinline__ uint32_t tg(float f) { return __float_as_uint(f) | 1u; }
__device__ __forceinline__ float uf(uint32_t w) { return __uint_as_float(w); }
__device__ __forceinline__ uint4 ldx128(const void* p) {
    uint4 v;
    asm volatile("ld.relaxed.gpu.global.v4.u32 {%0,%1,%2,%3}, [%4];" : "=r"(v.x), "=r"(v.y), "=r"(v.z), "=r"(v.w) : "l"(p) : "memory");
    return v;
}
__device__ __forceinline__ uint2 ldx64(const void* p) {
    uint2 v;
    asm volatile("ld.relaxed.gpu.global.v2.u32 {%0,%1}, [%2];" : "=r"(v.x), "=r"(v.y) : "l"(p) : "memory");
    return v;
}
__device__ __forceinline__ uint32_t ldx32(const void* p) {
    uint32_t v;
    asm volatile("ld.relaxed.gpu.global.u32 %0, [%1];" : "=r"(v) : "l"(p) : "memory");
    return v;
}
__device__ __forceinline__ void stx32(void* p, uint32_t v) { asm volatile("st.relaxed.gpu.global.u32 [%0], %1;" ::"l"(p), "r"(v) : "memory"); }
__device__ __forceinline__ void stx64(void* p, uint32_t a, uint32_t b) { asm volatile("st.relaxed.gpu.global.v2.u32 [%0], {%1,%2};" ::"l"(p), "r"(a), "r"(b) : "memory"); }
__device__ __forceinline__ void stx128(void* p, uint4 v) {
    asm volatile("st.relaxed.gpu.global.v4.u32 [%0], {%1,%2,%3,%4};" ::"l"(p), "r"(v.x), "r"(v.y), "r"(v.z), "r"(v.w) : "memory");
}
__device__ __forceinline__ void sts32(uint32_t a, uint32_t v) { asm volatile("st.shared.u32 [%0], %1;" ::"r"(a), "r"(v) : "memory"); }
__device__ __forceinline__ void sts16(uint32_t a, uint32_t v) { asm volatile("st.shared.u16 [%0], %1;" ::"r"(a), "h"((unsigned short)v) : "memory"); }
__device__ __forceinline__ void sts64f(uint32_t a, float x, float y) { asm volatile("st.shared.v2.f32 [%0], {%1,%2};" ::"r"(a), "f"(x), "f"(y) : "memory"); }
__device__ __forceinline__ void sts128f(uint32_t a, float x, float y, float z, float w) {
    asm volatile("st.shared.v4.f32 [%0], {%1,%2,%3,%4};" ::"r"(a), "f"(x), "f"(y), "f"(z), "f"(w) : "memory");
}
__device__ __forceinline__ float lds32f(uint32_t a) { float v; asm volatile("ld.shared.f32 %0, [%1];" : "=f"(v) : "r"(a) : "memory"); return v; }
__device__ __forceinline__ float2 lds64f(uint32_t a) { float2 v; asm volatile("ld.shared.v2.f32 {%0,%1}, [%2];" : "=f"(v.x), "=f"(v.y) : "r"(a) : "memory"); return v; }
__device__ __forceinline__ float4 lds128f(uint32_t a) {
    float4 v;
    asm volatile("ld.shared.v4.f32 {%0,%1,%2,%3}, [%4];" : "=f"(v.x), "=f"(v.y), "=f"(v.z), "=f"(v.w) : "r"(a) : "memory");
    return v;
}
__device__ __forceinline__ uint32_t keep(uint32_t v) { asm volatile("" : "+r"(v)); return v; }
template <typename T> __device__ __forceinline__ T* keep(T* p) { asm volatile("" : "+l"(p)); return p; }
__device__ __forceinline__ unsigned clock32() { unsigned c; asm volatile("mov.u32 %0, %clock;" : "=r"(c)); return c; }
__device__ __forceinline__ void wait_until(unsigned t0, unsigned n) {
    while (clock32() - t0 < n) __nanosleep(40);
}
__device__ __forceinline__ uint32_t and3(uint32_t a, uint32_t b, uint32_t c) {
    uint32_t d = a & b & c;
    asm("" : "+r"(d));
    return d;
}
__device__ __forceinline__ uint32_t umin2(uint32_t a, uint32_t b) { uint32_t d; asm("min.u32 %0, %1, %2;" : "=r"(d) : "r"(a), "r"(b)); return d; }
__device__ __forceinline__ uint32_t min4(const uint4& v) { return umin2(umin2(v.x, v.y), umin2(v.z, v.w)); }
__device__ __forceinline__ bool ok4(const uint4& v) { return min4(v) != 0; }
__device__ __forceinline__ uint32_t tag4(const uint4& v) { return and3(and3(v.x, v.y, v.z), v.w, v.w) & 1u; }
__device__ __forceinline__ uint32_t tag2(const uint2& v) { return and3(v.x, v.y, v.y) & 1u; }

template <int N>
__device__ __forceinline__ void bfly(float* a, int lane, int off) {
    const bool up = (lane & off) != 0;
#pragma unroll
    for (int i = 0; i < N / 2; i++) {
        float send = up ? a[i] : a[i + N / 2];
        float keep = up ? a[i + N / 2] : a[i];
        a[i] = keep + __shfl_xor_sync(0xffffffffu, send, off);
    }
}
__device__ __forceinline__ void unpack8(const uint4& v, float* f) {
    f[0] = bf_lo(v.x); f[1] = bf_hi(v.x); f[2] = bf_lo(v.y); f[3] = bf_hi(v.y);
    f[4] = bf_lo(v.z); f[5] = bf_hi(v.z); f[6] = bf_lo(v.w); f[7] = bf_hi(v.w);
}
__device__ __forceinline__ void stats8(const float* v, float& mean, float& m2) {
    mean = (((v[0] + v[1]) + (v[2] + v[3])) + ((v[4] + v[5]) + (v[6] + v[7]))) * 0.125f;
    float a = 0.f, b = 0.f;
#pragma unroll
    for (int i = 0; i < 4; i++) {
        const float d0 = v[i] - mean, d1 = v[4 + i] - mean;
        a = fmaf(d0, d0, a); b = fmaf(d1, d1, b);
    }
    m2 = a + b;
}
__device__ __forceinline__ void stats_merge(float& mean, float& m2, int off, float half_n) {
    const float mo = __shfl_xor_sync(0xffffffffu, mean, off), qo = __shfl_xor_sync(0xffffffffu, m2, off);
    const float d = mean - mo;
    m2 = fmaf(d * d, half_n, m2 + qo);
    mean = 0.5f * (mean + mo);
}
__device__ __forceinline__ void ln_finish(float mean, float m2, uint32_t& mean2, float& inv_sd) {
    const float var = m2 * (1.0f / DM);
    mean2 = pack_bf16(mean, mean);
    inv_sd = rcp(rbf(sqrt_a(rbf(rbf(var) + 1e-5f))));
}
__device__ __forceinline__ uint32_t ln_mod2(uint32_t x2, uint32_t mean2, float inv_sd, uint32_t opc2, uint32_t sh2) {
    const uint32_t d = bf2_sub(x2, mean2);
    const uint32_t n = pack_bf16(bf_lo(d) * inv_sd, bf_hi(d) * inv_sd);
    return bf2_add(bf2_mul(n, opc2), sh2);
}
__device__ __forceinline__ uint4 make_record(float v, int lane, int grp) {
    const float vn = __shfl_down_sync(0xffffffffu, v, 1);
    const uint32_t w = nz(pack_bf16(v, vn));
    const int src = (lane & 3) * 8;
    uint4 r;
    r.x = __shfl_sync(0xffffffffu, w, src + 2 * ((0 + grp) & 3));
    r.y = __shfl_sync(0xffffffffu, w, src + 2 * ((1 + grp) & 3));
    r.z = __shfl_sync(0xffffffffu, w, src + 2 * ((2 + grp) & 3));
    r.w = __shfl_sync(0xffffffffu, w, src + 2 * ((3 + grp) & 3));
    return r;
}
__device__ __forceinline__ void fold_halves(const float* d0, const float* d1, int t, float* r) {
#pragma unroll
    for (int i = 0; i < 4; i++) {
        const float v = (t < 2) ? d0[i] : d1[i];
        r[i] = v + __shfl_xor_sync(0xffffffffu, v, 2);
    }
}

__device__ __forceinline__ int krel_of(int w, int e, int lane) {
    return w * 64 + 8 * ((lane & 7) >> 1) + 2 * ((2 * e + (lane >> 4) + ((lane & 7) >> 1)) & 3) + (lane & 1);
}
__device__ __forceinline__ void load_silu(const bf16* cvec, int w, int g, int t, uint32_t* cw) {
    const uint32_t* cp = reinterpret_cast<const uint32_t*>(cvec) + (g & 3) * 256 + w * 32 + ((g >> 2) * 4 + t) * 4;
#pragma unroll
    for (int s = 0; s < 4; s++) cw[s] = __ldg(cp + ((s + t) & 3));
#pragma unroll
    for (int s = 0; s < 4; s++) {
        const float a = bf_lo(cw[s]), b = bf_hi(cw[s]);
        cw[s] = pack_bf16(__fdividef(a, 1.0f + __expf(-a)), __fdividef(b, 1.0f + __expf(-b)));
    }
}

__device__ __forceinline__ void ln_block_stats(const uint4& xv, uint32_t a_w, bool writer, uint32_t a_r, uint32_t& mean2, float& inv_sd) {
    float v[8], mean, m2;
    unpack8(xv, v);
    stats8(v, mean, m2);
    stats_merge(mean, m2, 1, 4.f);
    stats_merge(mean, m2, 2, 8.f);
    stats_merge(mean, m2, 16, 16.f);
    if (writer) sts64f(a_w, mean, m2);
    bar_sync(5, 256);
    float4 pw[4];
#pragma unroll
    for (int i = 0; i < 4; i++) pw[i] = lds128f(a_r + i * 16);
    mean = (((pw[0].x + pw[0].z) + (pw[1].x + pw[1].z)) + ((pw[2].x + pw[2].z) + (pw[3].x + pw[3].z))) * 0.125f;
    m2 = ((pw[0].y + pw[0].w) + (pw[1].y + pw[1].w)) + ((pw[2].y + pw[2].w) + (pw[3].y + pw[3].w));
    float dv0 = 0.f, dv1 = 0.f;
#pragma unroll
    for (int i = 0; i < 4; i++) {
        const float d0 = pw[i].x - mean, d1 = pw[i].z - mean;
        dv0 = fmaf(d0, d0, dv0); dv1 = fmaf(d1, d1, dv1);
    }
    ln_finish(mean, fmaf(dv0 + dv1, 64.0f, m2), mean2, inv_sd);
}

__device__ __forceinline__ void reduce_x1(int cgrp, int lane, float xown, float gate, unsigned delay) {
    const uint32_t* p = keep(g_t.wop + cgrp * (HQ * 32) + lane * 4);
    uint32_t* px = keep(&g_t.x1[((lane >> 2) * 64 + cgrp) * 16 + (lane & 3) * 4]);
    const uint32_t src = keep((uint32_t)((lane & 3) * 8 + 2 * (cgrp & 3)));
    uint4 v[8];
    uint32_t k[8];
#pragma unroll
    for (int i = 0; i < 8; i++) { k[i] = 0; v[i] = make_uint4(0, 0, 0, 0); }
    unsigned it = 0;
    uint32_t okw;
    bar_sync(6, 320);
    wait_until(clock32(), delay);
    do {
#pragma unroll
        for (int i = 0; i < 8; i++) if (!k[i]) v[i] = ldx128(p + i * 128);
#pragma unroll
        for (int i = 0; i < 8; i++) k[i] = tag4(v[i]);
        okw = and3(and3(k[0], k[1], k[2]), and3(k[3], k[4], k[5]), k[6] & k[7]);
    } while (!okw && ++it < SPIN_LIMIT);
    __syncwarp();
    float a[4];
    a[0] = ((uf(v[0].x) + uf(v[1].x)) + (uf(v[2].x) + uf(v[3].x))) + ((uf(v[4].x) + uf(v[5].x)) + (uf(v[6].x) + uf(v[7].x)));
    a[1] = ((uf(v[0].y) + uf(v[1].y)) + (uf(v[2].y) + uf(v[3].y))) + ((uf(v[4].y) + uf(v[5].y)) + (uf(v[6].y) + uf(v[7].y)));
    a[2] = ((uf(v[0].z) + uf(v[1].z)) + (uf(v[2].z) + uf(v[3].z))) + ((uf(v[4].z) + uf(v[5].z)) + (uf(v[6].z) + uf(v[7].z)));
    a[3] = ((uf(v[0].w) + uf(v[1].w)) + (uf(v[2].w) + uf(v[3].w))) + ((uf(v[4].w) + uf(v[5].w)) + (uf(v[6].w) + uf(v[7].w)));
    bfly<4>(a, lane, 16);
    bfly<2>(a, lane, 8);
    const float x1 = xown + rbf(gate * rbf(a[0]));
    const uint32_t w = nz(pack_bf16(x1, __shfl_down_sync(0xffffffffu, x1, 1)));
    uint4 r;
    r.x = __shfl_sync(0xffffffffu, w, src);
    r.y = __shfl_sync(0xffffffffu, w, (src & 24) | ((src + 2) & 7));
    r.z = __shfl_sync(0xffffffffu, w, src ^ 4);
    r.w = __shfl_sync(0xffffffffu, w, (src & 24) | ((src + 6) & 7));
    stx128(px, r);
}

__global__ void __launch_bounds__(NTHREADS, 1)
fused_kernel(const __grid_constant__ CUtensorMap tmK, const __grid_constant__ CUtensorMap tmV,
             const __grid_constant__ CUtensorMap tmM, const __grid_constant__ CUtensorMap tmQ,
             const __grid_constant__ CUtensorMap tmWo, const __grid_constant__ CUtensorMap tmG,
             const __grid_constant__ CUtensorMap tmU, const __grid_constant__ CUtensorMap tmD,
             const bf16* __restrict__ x, const bf16* __restrict__ cvec, bf16* __restrict__ out) {
    extern __shared__ uint8_t smem_raw[];
    const uint32_t sbase = keep((smem_u32(smem_raw) + 1023u) & ~1023u);
    uint8_t* sptr = smem_raw + (sbase - smem_u32(smem_raw));
    const int tid = (int)keep((uint32_t)threadIdx.x), lane = tid & 31, warp = tid >> 5;
    const int cta = blockIdx.x;
    const int odd = cta & 1, cgrp = cta >> 1;
    const uint32_t bar_full = sbase + OFF_BAR, bar_empty = bar_full + NSB * 8, bar_w = bar_empty + NSB * 8;
    const uint32_t bar_e = bar_w + NWBOX * 8, bar_wfree = bar_e + 4 * 8;
    volatile int* s_pace = reinterpret_cast<volatile int*>(sptr + OFF_PACE);
    if (warp == 10) {
        if (lane == 0) { s_pace[0] = 0; s_pace[1] = INFLIGHT; }
        __syncwarp();
        bar_sync(3, NTHREADS);
        if (lane == 0) {
            unsigned it = 0;
            int mine;
            do {
                __nanosleep(500);
                mine = s_pace[0];
                const int lag = (int)ldx32(&g_prog) - mine * NCTA - PACE_BIAS;
                if (mine > 0) s_pace[1] = INFLIGHT + (lag > PACE_LO) + (lag > PACE_HI) - (lag < -PACE_LO) - (lag < -PACE_HI);
            } while (mine < NKV - NSB - 1 && ++it < SPIN_LIMIT);
        }
        __syncwarp();
        if (!odd) {
            const float xown = __bfloat162float(x[(lane >> 3) * DM + cgrp * 8 + (lane & 7)]);
            bar_sync(2, 64);
            reduce_x1(cgrp, lane, xown, reinterpret_cast<float*>(sptr + OFF_LOC)[lane], H2DELAY + H2DUAL);
        } else {
            bar_arrive(6, 320);
        }
        return;
    }
    if (warp == 8) {
        uint64_t pol;
        asm volatile("createpolicy.fractional.L2::evict_first.b64 %0, 1.0;" : "=l"(pol));
        const int row0 = cta * (NTILE * TK);
        if (lane == 0) {
#pragma unroll
            for (int i = 0; i < 3; i++) mbar_init(bar_e + i * 8, 1);
#pragma unroll
            for (int i = 0; i < WIN0; i++) mbar_init(bar_full + i * 8, 1);
            asm volatile("fence.mbarrier_init.release.cluster;" ::: "memory");
            mbar_expect_tx(bar_full, SLOT);
            tma3d_hint(sbase, &tmK, 0, row0, 0, bar_full, pol);
            mbar_expect_tx(bar_e, 8192);
            tma2d(sbase + OFF_W, &tmM, odd * DM + cgrp * 8, 0, bar_e);
            tma2d(sbase + OFF_W + 4096, &tmM, odd * DM + cgrp * 8, 256, bar_e);
            mbar_expect_tx(bar_e + 8, SLOT);
            tma2d(sbase + OFF_WQ, &tmQ, cta * 32, 0, bar_e + 8);
            mbar_expect_tx(bar_e + 16, SLOT);
            tma2d(sbase + OFF_WQ + SLOT, &tmQ, cta * 32, 256, bar_e + 16);
            static_assert(WIN0 == 2, "two KV items are requested up front");
            mbar_expect_tx(bar_full + 8, SLOT);
            tma3d_hint(sbase + SLOT, &tmV, 0, row0, 0, bar_full + 8, pol);
        }
        __syncwarp();
        bar_sync(3, NTHREADS);
        if (lane == 0) {
            const int nbox = (cta < NFFN) ? NWBOX : 4;
            auto wbox = [&](int i) {
                const uint32_t dst = sbase + OFF_W + i * 8192, fb = bar_w + i * 8;
                mbar_expect_tx(fb, 8192);
                if (i < 4) tma2d(dst, &tmWo, (cta & 3) * 128 + (i >> 1) * 64, (cta >> 2) * 128 + (i & 1) * 64, fb);
                else if (i < 8) tma2d(dst, (i < 6) ? &tmG : &tmU, cta * 16, (i & 1) * 256, fb);
                else tma3d(dst, &tmD, 0, cta * 16, (i & 1) * 4, fb);
            };
            static_assert(LEAD0 >= NSB, "first lap in natural order");
#pragma unroll 1
            for (int i = WIN0; i < NSB; i++) {
                mbar_expect_tx(bar_full + i * 8, SLOT);
                unsigned it = 0;
                while (!mbar_test(bar_full + (i - WIN0) * 8, 0) && ++it < 16 * SPIN_LIMIT) {
                    if (mbar_test(bar_empty, 0) && (i < INFLIGHT || mbar_test(bar_full + (i - INFLIGHT) * 8, 0))) break;
                }
                tma3d_hint(sbase + off_of(i), (i & 1) ? &tmV : &tmK, 0, row0 + (i >> 1) * TK, 0, bar_full + i * 8, pol);
            }
            unsigned* gp = keep(&g_prog);
#pragma unroll 1
            for (int i = NSB; i < NKV; i++) {
                if (i >= DEFER0 && i < DEFER0 + 8 && !((i - DEFER0) & 1)) {
                    const int k = (i - DEFER0) >> 1;
                    if (k == 0) { mbar_wait(bar_empty + 8 * 8, 0); mbar_expect_tx(bar_e + 24, SLOT); }
                    tma2d(sbase + OFF_WM + k * 4096, &tmM, (2 + 2 * odd + (k >> 1)) * DM + cgrp * 8, (k & 1) * 256, bar_e + 24);
                    const CUtensorMap* m = k == 0 ? &tmWo : k == 1 ? &tmG : k == 2 ? &tmU : &tmD;
                    asm volatile("prefetch.tensormap [%0];" ::"l"(m) : "memory");
                }
                const int k = item_at(i), slot = bar_of(k);
                const uint32_t fb = bar_full + slot * 8, dst = sbase + slot * SLOT;
                const CUtensorMap* tm = (k & 1) ? &tmV : &tmK;
                const int row = row0 + (k >> 1) * TK;
                mbar_wait(bar_empty + slot * 8, (lap_of(k) & 1) ^ 1);
                mbar_expect_tx(fb, SLOT);
                const int w = item_at(i - s_pace[1]);
                mbar_wait(bar_full + bar_of(w) * 8, lap_of(w) & 1);
                tma3d_hint(dst, tm, 0, row, 0, fb, pol);
                asm volatile("red.relaxed.gpu.global.add.u32 [%0], 1;" ::"l"(gp) : "memory");
                s_pace[0] = i + 1 - NSB;
            }
            mbar_wait(bar_wfree, 0);
            mbar_wait(bar_empty + 9 * 8, 0);
            mbar_wait(bar_full + bar_of(NKV - 1) * 8, lap_of(NKV - 1) & 1);
#pragma unroll 1
            for (int i = 0; i < nbox; i++) {
                if (i >= 4) mbar_wait(bar_w + (i - WWIN) * 8, 0);
                wbox(i);
            }
        }
        return;
    }

    float* s_red = reinterpret_cast<float*>(sptr + OFF_RED);
    float* s_red2 = reinterpret_cast<float*>(sptr + OFF_RED2);
    float* s_loc = reinterpret_cast<float*>(sptr + OFF_LOC);
    const int g = lane >> 2, t = lane & 3;
    const int mch = (lane >> 3) & 1;

    if (warp == 9) {
        const int ob = lane >> 3, oc = lane & 7;
        const float xown = __bfloat162float(x[ob * DM + cgrp * 8 + oc]);
        if (lane == 0) {
#pragma unroll
            for (int i = WIN0; i < NSB; i++) mbar_init(bar_full + i * 8, 1);
#pragma unroll
            for (int i = 0; i < NSB; i++) mbar_init(bar_empty + i * 8, 4);
#pragma unroll
            for (int i = 0; i < NWBOX; i++) mbar_init(bar_w + i * 8, 1);
            mbar_init(bar_e + 24, 1);
            mbar_init(bar_wfree, 2);
            asm volatile("fence.mbarrier_init.release.cluster;" ::: "memory");
        }
        __syncwarp();
        bar_sync(3, NTHREADS);
        bar_sync(1, 288);
        {
            float u[8];
#pragma unroll
            for (int w = 0; w < 8; w++) u[w] = s_red2[w * 32 + oc * 4 + ob];
            float u0 = ((u[0] + u[1]) + (u[2] + u[3])) + ((u[4] + u[5]) + (u[6] + u[7]));
            if (odd) u0 = 1.0f + rbf(u0);
            const uint4 r = make_record(u0, lane, cgrp);
            stx128(&g_hd.sc[((odd * NREP + (lane >> 2)) * 64 + cgrp) * 16 + (lane & 3) * 4], r);
        }
        {
            constexpr int N16 = sizeof(TailScratch) / 16 / NCTA;
            uint4* p = reinterpret_cast<uint4*>(&g_t) + (size_t)cta * N16;
            const uint4 z = make_uint4(0, 0, 0, 0);
            __nanosleep(6000);
#pragma unroll 1
            for (int i = lane; i < N16; i += 32) p[i] = z;
            __threadfence();
            __syncwarp();
            if (lane == 0) atomicAdd(&g_cnt, 1u);
        }
        {
            float da[2][4] = {{0.f, 0.f, 0.f, 0.f}, {0.f, 0.f, 0.f, 0.f}};
            mbar_wait(bar_e + 24, 0);
#pragma unroll 1
            for (int w = 0; w < 8; w++) {
                const uint4 cw = *reinterpret_cast<const uint4*>(sptr + OFF_CW + (w * 32 + lane) * 16);
#pragma unroll
                for (int hf = 0; hf < 2; hf++) {
                    uint32_t a[4];
                    ldsm4t(a, sbase + OFF_WM + mch * 8192 + (krel_of(w, 0, lane) + hf * 32) * 16);
                    mma16816(da[hf], a, cw.x, cw.y);
                    ldsm4t(a, sbase + OFF_WM + mch * 8192 + (krel_of(w, 1, lane) + hf * 32) * 16);
                    mma16816(da[hf], a, cw.z, cw.w);
                }
            }
            __syncwarp();
            if (lane == 0) mbar_arrive(bar_wfree);
            float ra[4];
            fold_halves(da[0], da[1], t, ra);
            const int src = oc * 4 + (ob >> 1);
            const float a0 = __shfl_sync(0xffffffffu, ra[0], src), a1 = __shfl_sync(0xffffffffu, ra[1], src);
            const float b0 = __shfl_sync(0xffffffffu, ra[2], src), b1 = __shfl_sync(0xffffffffu, ra[3], src);
            const float va = rbf((ob & 1) ? a1 : a0), vb = rbf((ob & 1) ? b1 : b0);
            s_loc[lane] = odd ? vb : va;
            const uint4 r = make_record(odd ? 1.0f + va : vb, lane, cgrp);
            if (lane < 4) stx128(&g_hd.sbcb[(odd * 64 + cgrp) * 16 + lane * 4], r);
        }
        if (lane == 0) {
            unsigned it = 0;
            while (ldx32(&g_cnt) < (unsigned)NCTA && ++it < SPIN_LIMIT) __nanosleep(1000);
            __threadfence();
        }
        __syncwarp();
        bar_arrive(4, 288);
        const float gate = s_loc[lane];
        if (!odd) bar_arrive(2, 64);
        if (!odd) {
            reduce_x1(cgrp, lane, xown, gate, H2DELAY);
        } else {
            const uint32_t* xp = g_t.x1 + cgrp * 16 + ob * 4 + (((oc >> 1) - cgrp) & 3);
            bf16* po_ = keep(out + ob * DM + cgrp * 8 + oc);
            const uint32_t a_r = keep(sbase + OFF_RED2 + lane * 4);
            unsigned it = 0;
            uint32_t x1w;
            bar_sync(6, 320);
            do { __nanosleep(200); x1w = ldx32(xp); } while (!x1w && ++it < SPIN_LIMIT);
            const float x1 = (lane & 1) ? bf_hi(x1w) : bf_lo(x1w);
            bar_sync(7, 288);
            float f[8];
#pragma unroll
            for (int w = 0; w < 8; w++) f[w] = lds32f(a_r + w * 128);
            const float ffn = ((f[0] + f[1]) + (f[2] + f[3])) + ((f[4] + f[5]) + (f[6] + f[7]));
            *po_ = __float2bfloat16_rn(x1 + rbf(gate * rbf(ffn)));
            if (cta == 1 && lane == 0) { g_cnt = 0; g_prog = 0; }
        }
        return;
    }

    const int krel[2] = {krel_of(warp, 0, lane), krel_of(warp, 1, lane)};
    const int rec_off = (warp * 8 + (g >> 2) * 4 + t) * 16 + (g & 3) * 4;
    const int pair = cta >> 2, split = cta & 3;
    const int ab = pair >> 3, kvh = pair & 7;
    const uint32_t a_stw = keep(sbase + OFF_ST + (g * 8 + warp) * 8), a_str = keep(sbase + OFF_ST + (g & 3) * 64);
    const bool lane_st = t == 0 && g < 4;
    uint32_t qf[4][4];
    {
        const uint32_t* sp = g_hd.sc + ((cta >> 1) & (NREP - 1)) * 1024 + rec_off;
        const uint32_t* qp = g_hd.q + (ab * HQ + kvh * 4) * 64 + (tid & 63) * 4;
        uint4 sav = make_uint4(0, 0, 0, 0), cav = sav, qv = sav;
        float r[4];
        uint32_t cw[4];
        uint4 xv;
        {
            const uint32_t* xp = reinterpret_cast<const uint32_t*>(x) + (g & 3) * 256 + warp * 32 + ((g >> 2) * 4 + t) * 4;
            xv.x = __ldg(xp + (t & 3)); xv.y = __ldg(xp + ((1 + t) & 3)); xv.z = __ldg(xp + ((2 + t) & 3)); xv.w = __ldg(xp + ((3 + t) & 3));
        }
        load_silu(cvec, warp, g, t, cw);
        *reinterpret_cast<uint4*>(sptr + OFF_CW + tid * 16) = make_uint4(cw[0], cw[1], cw[2], cw[3]);
        uint32_t mean2;
        float inv_sd;
        ln_block_stats(xv, a_stw, lane_st, a_str, mean2, inv_sd);
        bar_sync(3, NTHREADS);
        mbar_wait(bar_e, 0);
        {
            float d[2][4];
#pragma unroll
            for (int hf = 0; hf < 2; hf++) {
                uint32_t a[2][4];
                ldsm4t(a[0], sbase + OFF_W + (krel[0] + hf * 32) * 16);
                ldsm4t(a[1], sbase + OFF_W + (krel[1] + hf * 32) * 16);
                mma16816z(d[hf], a[0], cw[0], cw[1]);
                mma16816(d[hf], a[1], cw[2], cw[3]);
            }
            fold_halves(d[0], d[1], t, r);
            if (t < 2) *reinterpret_cast<float2*>(s_red2 + warp * 32 + g * 4 + 2 * t) = make_float2(r[0], r[1]);
            bar_arrive(1, 288);
        }
        const unsigned t_a1 = clock32();
        uint32_t af[2][2][2][4];
        mbar_wait(bar_e + 8 + (warp >> 2) * 8, 0);
#pragma unroll
        for (int hf = 0; hf < 2; hf++)
#pragma unroll
            for (int e = 0; e < 2; e++) {
                const int k = krel[e] + hf * 32;
#pragma unroll
                for (int mt = 0; mt < 2; mt++)
                    ldsm4t(af[hf][e][mt], sbase + OFF_WQ + k * 64 + (((mt * 2 + mch) ^ ((k >> 1) & 3)) << 4));
            }
        {
            unsigned it = 0;
            wait_until(t_a1, SCDELAY);
            while (!(ok4(sav) && ok4(cav)) && ++it < SPIN_LIMIT) {
                sav = ldx128(sp); cav = ldx128(sp + NREP * 1024);
                if (!(ok4(sav) && ok4(cav))) __nanosleep(64);
            }
        }
        __syncwarp();
        const uint32_t h0 = ln_mod2(xv.x, mean2, inv_sd, cav.x, sav.x), h1 = ln_mod2(xv.y, mean2, inv_sd, cav.y, sav.y);
        const uint32_t h2 = ln_mod2(xv.z, mean2, inv_sd, cav.z, sav.z), h3 = ln_mod2(xv.w, mean2, inv_sd, cav.w, sav.w);
        float dq[2][2][4];
#pragma unroll
        for (int hf = 0; hf < 2; hf++)
#pragma unroll
            for (int mt = 0; mt < 2; mt++) {
                mma16816z(dq[hf][mt], af[hf][0][mt], h0, h1);
                mma16816(dq[hf][mt], af[hf][1][mt], h2, h3);
            }
#pragma unroll
        for (int mt = 0; mt < 2; mt++) {
            fold_halves(dq[0][mt], dq[1][mt], t, r);
            if (t < 2) {
                float* p = s_red + warp * 128 + 2 * t * 32 + mt * 16 + g;
                p[0] = r[0]; p[32] = r[1]; p[8] = r[2]; p[40] = r[3];
            }
        }
        bar_sync(5, 256);
        if (tid == 255) mbar_arrive(bar_wfree);
        if (tid < 64) {
            const int b = tid >> 4, cp2 = tid & 15;
            float s0 = 0.f, s1 = 0.f;
#pragma unroll
            for (int w = 0; w < 8; w++) {
                float2 v = *reinterpret_cast<const float2*>(s_red + w * 128 + b * 32 + 2 * cp2);
                s0 += v.x; s1 += v.y;
            }
            stx32(&g_hd.q[b * (HQ * 64) + cta * 16 + cp2], nz(pack_bf16(s0, s1)));
        }
        if (tid >= 64 && tid < 128) {
            const int i = tid - 64;
            unsigned it = 0;
            wait_until(clock32(), QDELAY);
            while (!ok4(qv) && ++it < SPIN_LIMIT) { qv = ldx128(qp); if (!ok4(qv)) __nanosleep(64); }
            *reinterpret_cast<uint4*>(sptr + OFF_SO + (i >> 4) * 272 + (i & 15) * 16) = qv;
        }
        bar_sync(5, 256);
#pragma unroll
        for (int kp = 0; kp < 4; kp++) ldsm4(qf[kp], sbase + OFF_SO + (lane & 3) * 272 + kp * 64 + (lane >> 3) * 16);
    }

    constexpr int MS0 = off_of(NKV - 4), MS1 = off_of(NKV - 2);
    const int hd = tid >> 6, dp = tid & 63, hh = cta >> 2;
    const uint32_t a_mrgw = keep(sbase + ((warp >> 2) ? MS1 : MS0) + (t & 1) * (8192 + 32) + (warp & 3) * 2048 + g * (MRG_G * 4));
    const uint32_t a_mrgr = keep(sbase + (hd >> 1) * (8192 + 32) + ((hd & 1) * MRG_H + ((2 * dp) & 7) * MRG_G + (dp >> 2)) * 4);
    const uint32_t a_sow = keep(sbase + OFF_SO + hd * 272 + dp * 4);
    const uint32_t a_sor = keep(sbase + OFF_SO + (lane & 3) * 272 + (lane >> 3) * 16);
    const uint32_t a_redw = keep(sbase + OFF_RED + (warp * 128 + g * 8 + (t & 1) * 4 + (t >> 1) * 64) * 4);
    const uint32_t a_redr = keep(sbase + OFF_RED + tid * 8);
    const uint32_t a_actw = keep(sbase + OFF_ACT + (tid & 3) * 48 + (tid >> 2) * 2);
    const uint32_t a_actr = keep(sbase + OFF_ACT + (lane & 3) * 48 + mch * 16);
    const uint32_t a_red2w = keep(sbase + OFF_RED2 + tid * 4);
    uint32_t* w_po = keep(&g_t.po[(((kvh * 4 + hd) * NB + ab) * 4 + split) * DH + 2 * dp]);
    const uint32_t* r_po = keep(g_t.po + (hh * NB + hd) * 4 * DH + 2 * dp);
    const uint32_t* r_ml = keep(g_t.pml + (hh * NB + hd) * 8);
    uint32_t* w_wop = keep(g_t.wop + (((cta & 3) * 16 + warp * 2 + (t >> 1)) * HQ + hh) * 32 + g * 4 + 2 * (t & 1));
    const uint32_t* r_x1 = keep(g_t.x1 + (cta & (NREP - 1)) * 1024 + rec_off);
    uint32_t* w_dnp = keep(g_t.dnp + ((warp * 8 + (t >> 1)) * NFFN + cta) * 32 + g * 4 + 2 * (t & 1));
    const uint32_t* r_dnp = keep(g_t.dnp + cgrp * (NFFN * 32) + tid * 4);
    const bool lo2 = t < 2;

    float o[8][4];
#pragma unroll
    for (int i = 0; i < 8; i++) { o[i][0] = o[i][1] = o[i][2] = o[i][3] = 0.f; }
    uint4 sbv, cbv;
    {
        float m0 = -INFINITY, m1 = -INFINITY, l0 = 0.f, l1 = 0.f;
        const int grp = warp >> 2, r0 = (warp & 3) * 16;
        const int krow = r0 + (lane & 7) + ((lane >> 3) & 1) * 8;
        const int vrow = r0 + (lane & 7) + (lane >> 4) * 8;
        const uint32_t koff = krow * 128, kx = krow & 7, kc = lane >> 4;
        const uint32_t voff = vrow * 128, vx = vrow & 7, vc = (lane >> 3) & 1;
        int slot, ph;
        uint32_t kb;
        const float scale = 0.08838834764831845f;
        uint32_t b0, b1;
#pragma unroll 1
        for (int j = grp;; j += 2) {
            slot = bar_of(2 * j); ph = lap_of(2 * j) & 1; kb = sbase + off_of(2 * j);
            const bool handover = lap_of(2 * j) == 1;
            if (handover) mbar_wait(bar_empty + slot * 8, 0);
            mbar_wait(bar_full + slot * 8, ph);
            float s[2][4];
#pragma unroll
            for (int ks = 0; ks < 8; ks++) {
                uint32_t a[4];
                ldsm4(a, kb + (ks >> 2) * 8192 + koff + ((((ks & 3) * 2 + kc) ^ kx) << 4));
                if (ks < 2) mma16816z(s[ks & 1], a, qf[ks >> 1][(ks & 1) * 2], qf[ks >> 1][(ks & 1) * 2 + 1]);
                else mma16816(s[ks & 1], a, qf[ks >> 1][(ks & 1) * 2], qf[ks >> 1][(ks & 1) * 2 + 1]);
            }
            __syncwarp();
            if (lane == 0) mbar_arrive(bar_empty + slot * 8);
            float sv[4];
#pragma unroll
            for (int i = 0; i < 4; i++) sv[i] = rbf(rbf(s[0][i] + s[1][i]) * scale);
            float t0 = fmaxf(sv[0], sv[2]), t1 = fmaxf(sv[1], sv[3]);
#pragma unroll
            for (int off = 4; off < 32; off <<= 1) {
                t0 = fmaxf(t0, __shfl_xor_sync(0xffffffffu, t0, off));
                t1 = fmaxf(t1, __shfl_xor_sync(0xffffffffu, t1, off));
            }
            const float n0 = fmaxf(m0, t0), n1 = fmaxf(m1, t1);
            if (__any_sync(0xffffffffu, (n0 != m0) || (n1 != m1))) {
                const float a0 = ex2((m0 - n0) * LOG2E), a1 = ex2((m1 - n1) * LOG2E);
                l0 *= a0; l1 *= a1;
#pragma unroll
                for (int i = 0; i < 8; i++) { o[i][0] *= a0; o[i][1] *= a1; o[i][2] *= a0; o[i][3] *= a1; }
                m0 = n0; m1 = n1;
            }
            const float p0 = ex2((sv[0] - m0) * LOG2E), p1 = ex2((sv[1] - m1) * LOG2E);
            const float p2 = ex2((sv[2] - m0) * LOG2E), p3 = ex2((sv[3] - m1) * LOG2E);
            l0 += p0 + p2; l1 += p1 + p3;
            b0 = movmat(pack_bf16(p0, p1)); b1 = movmat(pack_bf16(p2, p3));
            if (j >= NTILE - 2) break;
            if (handover) mbar_wait(bar_empty + slot * 8 + 8, 0);
            mbar_wait(bar_full + slot * 8 + 8, ph);
#pragma unroll
            for (int mt = 0; mt < 8; mt++) {
                uint32_t a[4];
                ldsm4t(a, kb + SLOT + (mt >> 2) * 8192 + voff + ((((mt & 3) * 2 + vc) ^ vx) << 4));
                mma16816(o[mt], a, b0, b1);
            }
            __syncwarp();
            if (lane == 0) mbar_arrive(bar_empty + slot * 8 + 8);
        }
#pragma unroll
        for (int off = 4; off < 32; off <<= 1) {
            l0 += __shfl_xor_sync(0xffffffffu, l0, off);
            l1 += __shfl_xor_sync(0xffffffffu, l1, off);
        }
        if (lane < 2) sts128f(sbase + OFF_ML + (warp * 4 + 2 * t) * 8, m0, l0, m1, l1);
        sbv = ldx128(g_hd.sbcb + rec_off);
        cbv = ldx128(g_hd.sbcb + 1024 + rec_off);
        bar_sync(4, 288);
        float f[8];
        {
            float2 ml[8];
#pragma unroll
            for (int w = 0; w < 8; w++) ml[w] = lds64f(sbase + OFF_ML + (w * 4 + hd) * 8);
            const float M = fmaxf(fmaxf(fmaxf(ml[0].x, ml[1].x), fmaxf(ml[2].x, ml[3].x)), fmaxf(fmaxf(ml[4].x, ml[5].x), fmaxf(ml[6].x, ml[7].x)));
            float L = 0.f;
#pragma unroll
            for (int w = 0; w < 8; w++) { f[w] = ex2((ml[w].x - M) * LOG2E); L = fmaf(f[w], ml[w].y, L); }
            if (dp == 0) stx64(&g_t.pml[(((kvh * 4 + hd) * NB + ab) * 4 + split) * 2], tg(M), tg(L));
        }
        mbar_wait(bar_full + slot * 8 + 8, ph);
#pragma unroll
        for (int mt = 0; mt < 8; mt++) {
            uint32_t a[4];
            ldsm4t(a, kb + SLOT + (mt >> 2) * 8192 + voff + ((((mt & 3) * 2 + vc) ^ vx) << 4));
            mma16816(o[mt], a, b0, b1);
        }
        {
            const uint32_t aw = a_mrgw + (lo2 ? 0 : MRG_H * 4);
#pragma unroll
            for (int i = 0; i < 4; i++)
                sts128f(aw + i * 16, lo2 ? o[2 * i][0] : o[2 * i][1], lo2 ? o[2 * i][2] : o[2 * i][3],
                        lo2 ? o[2 * i + 1][0] : o[2 * i + 1][1], lo2 ? o[2 * i + 1][2] : o[2 * i + 1][3]);
        }
        bar_sync(5, 256);
        float a0[2] = {0.f, 0.f}, a1[2] = {0.f, 0.f};
#pragma unroll
        for (int w = 0; w < 8; w++) {
            const uint32_t ar = a_mrgr + ((w >> 2) ? MS1 : MS0) + (w & 3) * 2048;
            a0[w & 1] = fmaf(f[w], lds32f(ar), a0[w & 1]);
            a1[w & 1] = fmaf(f[w], lds32f(ar + MRG_G * 4), a1[w & 1]);
        }
        stx64(w_po, tg(a0[0] + a0[1]), tg(a1[0] + a1[1]));
    }
    const unsigned t_po = clock32();
    {
        unsigned it = 0;
        const int half = warp >> 2;
        uint32_t af[8][4];
        const int wrow = (lane & 7) + (lane >> 4) * 8;
        const uint32_t a_wo = sbase + OFF_W + half * SLOT + wrow * 128 + ((((warp & 3) * 2 + mch) ^ (wrow & 7)) << 4);
        bool early = false;
        while (!(ok4(sbv) && ok4(cbv)) && ++it < SPIN_LIMIT) {
            sbv = ldx128(g_hd.sbcb + rec_off);
            cbv = ldx128(g_hd.sbcb + 1024 + rec_off);
        }
        uint2 v[4] = {make_uint2(0, 0), make_uint2(0, 0), make_uint2(0, 0), make_uint2(0, 0)};
        uint4 ml0 = make_uint4(0, 0, 0, 0), ml1 = ml0;
        uint32_t k[6] = {0, 0, 0, 0, 0, 0}, okw;
        wait_until(t_po, H1DELAY);
        do {
#pragma unroll
            for (int s = 0; s < 4; s++) if (!k[s]) v[s] = ldx64(r_po + s * DH);
            if (!k[4]) ml0 = ldx128(r_ml);
            if (!k[5]) ml1 = ldx128(r_ml + 4);
            __syncwarp();
            if (!early && __all_sync(0xffffffffu, mbar_test(bar_w + (2 * half) * 8, 0) && mbar_test(bar_w + (2 * half + 1) * 8, 0))) {
#pragma unroll
                for (int ks = 0; ks < 8; ks++) ldsm4t(af[ks], a_wo + ks * 2048);
                early = true;
            }
#pragma unroll
            for (int s = 0; s < 4; s++) k[s] = tag2(v[s]);
            k[4] = tag4(ml0); k[5] = tag4(ml1);
            okw = and3(k[0], k[1], k[2]) & and3(k[3], k[4], k[5]);
        } while (!__all_sync(0xffffffffu, okw) && ++it < SPIN_LIMIT);
        const float M = fmaxf(fmaxf(uf(ml0.x), uf(ml0.z)), fmaxf(uf(ml1.x), uf(ml1.z)));
        const float f0 = ex2((uf(ml0.x) - M) * LOG2E), f1 = ex2((uf(ml0.z) - M) * LOG2E);
        const float f2 = ex2((uf(ml1.x) - M) * LOG2E), f3 = ex2((uf(ml1.z) - M) * LOG2E);
        const float inv = rcp(fmaf(f0, uf(ml0.y), f1 * uf(ml0.w)) + fmaf(f2, uf(ml1.y), f3 * uf(ml1.w)));
        const float o0 = fmaf(f0, uf(v[0].x), f1 * uf(v[1].x)) + fmaf(f2, uf(v[2].x), f3 * uf(v[3].x));
        const float o1 = fmaf(f0, uf(v[0].y), f1 * uf(v[1].y)) + fmaf(f2, uf(v[2].y), f3 * uf(v[3].y));
        sts32(a_sow, pack_bf16(o0 * inv, o1 * inv));
        __syncwarp();
        if (!early) {
            mbar_wait(bar_w + (2 * half) * 8, 0);
            mbar_wait(bar_w + (2 * half + 1) * 8, 0);
#pragma unroll
            for (int ks = 0; ks < 8; ks++) ldsm4t(af[ks], a_wo + ks * 2048);
        }
        bar_sync(5, 256);
        float d[4][4];
        uint32_t bf[4][4];
#pragma unroll
        for (int kp = 0; kp < 4; kp++) ldsm4(bf[kp], a_sor + kp * 64);
#pragma unroll
        for (int kp = 0; kp < 4; kp++) mma16816z(d[kp], af[2 * kp], bf[kp][0], bf[kp][1]);
#pragma unroll
        for (int kp = 0; kp < 4; kp++) mma16816(d[kp], af[2 * kp + 1], bf[kp][2], bf[kp][3]);
        const float e0 = lo2 ? (d[0][0] + d[1][0]) + (d[2][0] + d[3][0]) : (d[0][2] + d[1][2]) + (d[2][2] + d[3][2]);
        const float e1 = lo2 ? (d[0][1] + d[1][1]) + (d[2][1] + d[3][1]) : (d[0][3] + d[1][3]) + (d[2][3] + d[3][3]);
        stx64(w_wop, tg(e0), tg(e1));
    }
    const unsigned t_wop = clock32();
    bar_arrive(6, 320);
    if (cta < NFFN) {
        constexpr int OG = OFF_W + 2 * SLOT, OU = OFF_W + 3 * SLOT, OD = OFF_W + 4 * SLOT;
        uint32_t ag[2][2][4], au[2][2][4];
        mbar_wait(bar_w + (4 + (warp >> 2)) * 8, 0);
        mbar_wait(bar_w + (6 + (warp >> 2)) * 8, 0);
#pragma unroll
        for (int hf = 0; hf < 2; hf++)
#pragma unroll
            for (int e = 0; e < 2; e++) {
                const int k = krel[e] + hf * 32;
                const uint32_t off = k * 32 + ((mch ^ ((k >> 2) & 1)) << 4);
                ldsm4t(ag[hf][e], sbase + OG + off);
                ldsm4t(au[hf][e], sbase + OU + off);
            }
        uint32_t ad[4][4];
        bool have_dn = false;
        auto load_dn = [&]() {
            const int krow = (lane & 7) + (lane >> 4) * 8;
#pragma unroll
            for (int mt = 0; mt < 4; mt++)
                ldsm4t(ad[mt], sbase + OD + warp * 2048 + krow * 128 + (((mt * 2 + mch) ^ (krow & 7)) << 4));
        };
        uint32_t hw[4];
        {
            unsigned it = 0;
            wait_until(t_wop, H3DELAY - 200);
            if (__all_sync(0xffffffffu, mbar_test(bar_w + (8 + (warp >> 2)) * 8, 0))) { load_dn(); have_dn = true; }
            uint4 xv = ldx128(r_x1);
            while (!ok4(xv) && ++it < SPIN_LIMIT) xv = ldx128(r_x1);
            __syncwarp();
            uint32_t mean2;
            float inv_sd;
            ln_block_stats(xv, a_stw, lane_st, a_str, mean2, inv_sd);
            hw[0] = ln_mod2(xv.x, mean2, inv_sd, cbv.x, sbv.x);
            hw[1] = ln_mod2(xv.y, mean2, inv_sd, cbv.y, sbv.y);
            hw[2] = ln_mod2(xv.z, mean2, inv_sd, cbv.z, sbv.z);
            hw[3] = ln_mod2(xv.w, mean2, inv_sd, cbv.w, sbv.w);
        }
        {
            float dg[2][4], du[2][4], rg[4], ru[4];
#pragma unroll
            for (int hf = 0; hf < 2; hf++) {
                mma16816z(dg[hf], ag[hf][0], hw[0], hw[1]);
                mma16816z(du[hf], au[hf][0], hw[0], hw[1]);
            }
#pragma unroll
            for (int hf = 0; hf < 2; hf++) {
                mma16816(dg[hf], ag[hf][1], hw[2], hw[3]);
                mma16816(du[hf], au[hf][1], hw[2], hw[3]);
            }
            fold_halves(dg[0], dg[1], t, rg);
            fold_halves(du[0], du[1], t, ru);
            sts128f(a_redw, lo2 ? rg[0] : rg[2], lo2 ? ru[0] : ru[2], lo2 ? rg[1] : rg[3], lo2 ? ru[1] : ru[3]);
        }
        bar_sync(5, 256);
        if (warp < 2) {
            float2 v[8];
#pragma unroll
            for (int w = 0; w < 8; w++) v[w] = lds64f(a_redr + w * 512);
            const float gv = rbf(((v[0].x + v[1].x) + (v[2].x + v[3].x)) + ((v[4].x + v[5].x) + (v[6].x + v[7].x)));
            const float uv = rbf(((v[0].y + v[1].y) + (v[2].y + v[3].y)) + ((v[4].y + v[5].y) + (v[6].y + v[7].y)));
            const float inner = 0.7978845608028654f * (gv + 0.044715f * gv * gv * gv);
            const float th = 1.0f - 2.0f * rcp(ex2(inner * (2.0f * LOG2E)) + 1.0f);
            const float ge = rbf(0.5f * gv * (1.0f + th));
            sts16(a_actw, pack_bf16(ge * uv, 0.f));
        } else if (cta < 104 && tid >= 192) {
            reinterpret_cast<uint4*>(&g_hd)[cta * 64 + tid - 192] = make_uint4(0, 0, 0, 0);
        }
        if (!have_dn) {
            mbar_wait(bar_w + (8 + (warp >> 2)) * 8, 0);
            load_dn();
        }
        bar_sync(5, 256);
        {
            uint32_t bf[2];
            ldsm2(bf, a_actr);
#pragma unroll
            for (int mt = 0; mt < 4; mt++) {
                float d[4];
                mma16816z(d, ad[mt], bf[0], bf[1]);
                stx64(w_dnp + (2 * mt) * (NFFN * 32), tg(lo2 ? d[0] : d[2]), tg(lo2 ? d[1] : d[3]));
            }
        }
    }
    if (odd) {
        unsigned it = 0;
        if (cta >= NFFN) __nanosleep(1000);
        wait_until(clock32(), H4DELAY);
        uint4 v[4];
        v[0] = v[1] = v[2] = make_uint4(0, 0, 0, 0);
        v[3] = make_uint4(1u, 1u, 1u, 1u);
        uint32_t k[4] = {0, 0, 0, warp < 4 ? 0u : 1u}, okw;
        do {
#pragma unroll
            for (int i = 0; i < 4; i++) if (!k[i]) v[i] = ldx128(r_dnp + i * 1024);
#pragma unroll
            for (int i = 0; i < 4; i++) k[i] = tag4(v[i]);
            okw = and3(k[0], k[1], k[2]) & k[3];
        } while (!okw && ++it < SPIN_LIMIT);
        __syncwarp();
        float a[4];
        a[0] = (uf(v[0].x) + uf(v[1].x)) + (uf(v[2].x) + uf(v[3].x));
        a[1] = (uf(v[0].y) + uf(v[1].y)) + (uf(v[2].y) + uf(v[3].y));
        a[2] = (uf(v[0].z) + uf(v[1].z)) + (uf(v[2].z) + uf(v[3].z));
        a[3] = (uf(v[0].w) + uf(v[1].w)) + (uf(v[2].w) + uf(v[3].w));
        bfly<4>(a, lane, 16);
        bfly<2>(a, lane, 8);
        sts32(a_red2w, __float_as_uint(a[0]));
        bar_arrive(7, 288);
    }
}

typedef CUresult (*EncodeFn)(CUtensorMap*, CUtensorMapDataType, cuuint32_t, void*, const cuuint64_t*, const cuuint64_t*,
                             const cuuint32_t*, const cuuint32_t*, CUtensorMapInterleave, CUtensorMapSwizzle,
                             CUtensorMapL2promotion, CUtensorMapFloatOOBfill);

void encode(EncodeFn fn, CUtensorMap* m, const void* base, int rank, const cuuint64_t* dims, const cuuint64_t* strides,
            const cuuint32_t* box, CUtensorMapSwizzle sw, CUtensorMapL2promotion promo) {
    cuuint32_t es[3] = {1, 1, 1};
    fn(m, CU_TENSOR_MAP_DATA_TYPE_BFLOAT16, rank, const_cast<void*>(base), dims, strides, box, es,
       CU_TENSOR_MAP_INTERLEAVE_NONE, sw, promo, CU_TENSOR_MAP_FLOAT_OOB_FILL_NONE);
}

}

extern "C" void kernel_launch(void* const* d_in, const int* in_sizes, int n_in, void* d_out, int out_size) {
    (void)in_sizes; (void)n_in; (void)out_size;
    const bf16* x = (const bf16*)d_in[0];
    const bf16* kc = (const bf16*)d_in[1];
    const bf16* vc = (const bf16*)d_in[2];
    const bf16* wq = (const bf16*)d_in[3];
    const bf16* wo = (const bf16*)d_in[4];
    const bf16* wg = (const bf16*)d_in[6];
    const bf16* wu = (const bf16*)d_in[7];
    const bf16* wd = (const bf16*)d_in[8];
    const bf16* cv = (const bf16*)d_in[9];
    const bf16* wm = (const bf16*)d_in[10];

    static EncodeFn fn = nullptr;
    if (!fn) {
        void* p = nullptr;
        cudaDriverEntryPointQueryResult st;
        cudaGetDriverEntryPoint("cuTensorMapEncodeTiled", &p, cudaEnableDefault, &st);
        fn = (EncodeFn)p;
        cudaFuncSetAttribute(fused_kernel, cudaFuncAttributeMaxDynamicSharedMemorySize, SMEM_BYTES);
    }
    CUtensorMap tmK, tmV, tmM, tmQ, tmWo, tmG, tmU, tmD;
    {
        cuuint64_t dims[2] = {6 * DM, DM};
        cuuint64_t strides[1] = {6 * DM * 2};
        cuuint32_t box[2] = {8, 256};
        encode(fn, &tmM, wm, 2, dims, strides, box, CU_TENSOR_MAP_SWIZZLE_NONE, CU_TENSOR_MAP_L2_PROMOTION_L2_128B);
    }
    {
        cuuint64_t dims[2] = {HQ * DH, DM};
        cuuint64_t strides[1] = {HQ * DH * 2};
        cuuint32_t box[2] = {32, 256};
        encode(fn, &tmQ, wq, 2, dims, strides, box, CU_TENSOR_MAP_SWIZZLE_64B, CU_TENSOR_MAP_L2_PROMOTION_L2_128B);
    }
    {
        cuuint64_t dims[3] = {64, (cuuint64_t)NB * HKV * SK, 2};
        cuuint64_t strides[2] = {256, 128};
        cuuint32_t box[3] = {64, TK, 2};
        encode(fn, &tmK, kc, 3, dims, strides, box, CU_TENSOR_MAP_SWIZZLE_128B, CU_TENSOR_MAP_L2_PROMOTION_L2_256B);
        encode(fn, &tmV, vc, 3, dims, strides, box, CU_TENSOR_MAP_SWIZZLE_128B, CU_TENSOR_MAP_L2_PROMOTION_L2_256B);
    }
    {
        cuuint64_t dims[2] = {DM, HQ * DH};
        cuuint64_t strides[1] = {DM * 2};
        cuuint32_t box[2] = {64, 64};
        encode(fn, &tmWo, wo, 2, dims, strides, box, CU_TENSOR_MAP_SWIZZLE_128B, CU_TENSOR_MAP_L2_PROMOTION_L2_256B);
    }
    {
        cuuint64_t dims[2] = {FF, DM};
        cuuint64_t strides[1] = {FF * 2};
        cuuint32_t box[2] = {16, 256};
        encode(fn, &tmG, wg, 2, dims, strides, box, CU_TENSOR_MAP_SWIZZLE_32B, CU_TENSOR_MAP_L2_PROMOTION_L2_128B);
        encode(fn, &tmU, wu, 2, dims, strides, box, CU_TENSOR_MAP_SWIZZLE_32B, CU_TENSOR_MAP_L2_PROMOTION_L2_128B);
    }
    {
        cuuint64_t dims[3] = {64, FF, 8};
        cuuint64_t strides[2] = {DM * 2, 128};
        cuuint32_t box[3] = {64, 16, 4};
        encode(fn, &tmD, wd, 3, dims, strides, box, CU_TENSOR_MAP_SWIZZLE_128B, CU_TENSOR_MAP_L2_PROMOTION_L2_256B);
    }
    fused_kernel<<<NCTA, NTHREADS, SMEM_BYTES>>>(tmK, tmV, tmM, tmQ, tmWo, tmG, tmU, tmD, x, cv, (bf16*)d_out);
}
```
